```python
import torch

def _softmax(x, axis=-1):
    return torch.softmax(x, dim=axis)
def _gelu(x):
    return torch.nn.functional.gelu(x, approximate="tanh")
def _silu(x):
    return torch.nn.functional.silu(x)
def _sigmoid(x):
    return torch.sigmoid(x)
def _layernorm(x, axis=-1, eps=1e-5):
    m = x.mean(dim=axis, keepdim=True)
    v = x.var(dim=axis, keepdim=True, unbiased=False)
    return (x - m) / torch.sqrt(v + eps)
def _scatter_add(tgt, idx, src, axis=0):
    return tgt.clone().index_add_(axis, idx, src)
def _segment_sum(src, seg, n):
    out = torch.zeros((n,) + src.shape[1:], dtype=src.dtype)
    return out.index_add_(0, seg, src)
def _pad(x, pw):
    flat = tuple(v for pair in reversed(pw) for v in pair)
    return torch.nn.functional.pad(x, flat)

kernel_name = 'standalone__linear_attn_block__prompt'

def setup_inputs():

    _w = (lambda a: (lambda t: t.to(torch.bfloat16) if t.is_floating_point() else t)(torch.as_tensor(a)))
    B, S, D = 1, 2048, 576
    return {
        "x": _w((lambda *s: torch.randn(*s, dtype=torch.bfloat16) * 0.05)(B, S, D)),
        "wqkv": _w((lambda *s: torch.randn(*s, dtype=torch.bfloat16) * 0.4)(D, 3 * D)),
        "wo": _w((lambda *s: torch.randn(*s, dtype=torch.bfloat16) * 0.05)(D, D)),
    }

def reference(x, wqkv, wo):
    B, S, D = x.shape
    H = 32; Dh = D // H
    qkv = (lambda x, *d: x.permute(*d))((x @ wqkv).reshape(B, S, 3, H, Dh), 2, 0, 3, 1, 4)
    q, k, v = qkv[0], qkv[1], qkv[2]
    phi = lambda t: torch.where(t > 0, t + 1, torch.exp(t)) + 1e-6
    pq, pk = phi(q), phi(k)
    kv = torch.einsum("bhsd,bhse->bhde", pk, v)
    z = torch.einsum("bhsd->bhd", pk)
    num = torch.einsum("bhqd,bhde->bhqe", pq, kv)
    den = torch.einsum("bhqd,bhd->bhq", pq, z)[..., None] + 1e-6
    o = num / den
    return (lambda x, *d: x.permute(*d))(o, 0, 2, 1, 3).reshape(B, S, D) @ wo
```

```cpp
#include <cuda_runtime.h>
#include <cuda_bf16.h>
#include <cuda.h>
#include <stdint.h>
#include <type_traits>

namespace {

constexpr uint32_t TAB_K = 0x00765696u, TAB_V = 0xC612B6A6u, TAB_X = 0x26866646u;
__host__ __device__ constexpr int slot(uint32_t tab, int s) { return (int)((tab >> (8 * (s & 3))) & 255) * 1024; }
__host__ __device__ constexpr int slot_x(int c) { return c == 0 ? 54 * 1024 : slot(TAB_X, c - 1); }
constexpr int OFF_PK = 0, OFF_V = 18432;
__host__ __device__ constexpr int tile_q(int j) { return (54 + 18 * j) * 1024; }
__host__ __device__ constexpr int tile_o(int p) { return 27648 * p; }
constexpr int OFF_BKV = 218 * 1024;
constexpr int OFF_BAR = OFF_BKV + 7680;
constexpr int SMEM_BYTES = 232448;
constexpr int B_F0 = 0;
constexpr int B_FULL = 1;
constexpr int B_INIT = 20;
constexpr int B_EMP = 24;
#define Q_A 3
#define Q_B 4
#define Q_GO 34
#define KV_AT 0
#define DELAY_EARLY 900
#define DELAY_LATE 700
constexpr uint32_t SENT = 0xFFFFFFFFu;
constexpr int SPIN_LIMIT = 1 << 17;

struct __align__(65536) Scratch {
    uint4 o[32 * 4 * 8 * 128];
    uint2 oh[32 * 8 * 128];
    float4 kv[8 * 2 * 4 * 96];
    unsigned init;
};
__device__ Scratch g_scratch;
#define GT(i) do {} while (0)
#define CLK(v) do {} while (0)
#define PUT(i, v) do {} while (0)
#define STAMP(i) do {} while (0)
#define STAMPW(i) do {} while (0)
#define DUMP(lo, hi, step) do {} while (0)

__device__ __forceinline__ void mbar_init(uint32_t bar, uint32_t cnt) { asm volatile("mbarrier.init.shared::cta.b64 [%0], %1;" :: "r"(bar), "r"(cnt) : "memory"); }
__device__ __forceinline__ void mbar_arrive(uint32_t bar) { asm volatile("mbarrier.arrive.shared::cta.b64 _, [%0];" :: "r"(bar) : "memory"); }
__device__ __forceinline__ void mbar_wait(uint32_t bar) {
    asm volatile("{ .reg .pred p;\n"
                 "W: mbarrier.try_wait.parity.shared::cta.b64 p, [%0], 0;\n"
                 "@!p bra.uni W; }" :: "r"(bar) : "memory");
}
__device__ __forceinline__ bool elect() {
    uint32_t p; asm volatile("{ .reg .pred q; elect.sync _|q, 0xffffffff; selp.u32 %0, 1, 0, q; }" : "=r"(p)); return p;
}
__device__ __forceinline__ void mbar_expect(uint32_t bar, uint32_t bytes) { asm volatile("mbarrier.arrive.expect_tx.shared::cta.b64 _, [%0], %1;" :: "r"(bar), "r"(bytes) : "memory"); }
__device__ __forceinline__ void tma4(uint32_t dst, const CUtensorMap* m, int c0, int c1, int c2, int c3, uint32_t bar) {
    asm volatile("cp.async.bulk.tensor.4d.shared::cluster.global.mbarrier::complete_tx::bytes [%0], [%1, {%3, %4, %5, %6}], [%2];"
                 :: "r"(dst), "l"(m), "r"(bar), "r"(c0), "r"(c1), "r"(c2), "r"(c3) : "memory");
}
__device__ __forceinline__ void tma_st2(const CUtensorMap* m, uint32_t src, int c0, int c1) {
    asm volatile("cp.async.bulk.tensor.2d.global.shared::cta.bulk_group [%0, {%2, %3}], [%1];" :: "l"(m), "r"(src), "r"(c0), "r"(c1) : "memory");
}
__device__ __forceinline__ void tma_st3(const CUtensorMap* m, uint32_t src, int c0, int c1, int c2) {
    asm volatile("cp.async.bulk.tensor.3d.global.shared::cta.bulk_group [%0, {%2, %3, %4}], [%1];" :: "l"(m), "r"(src), "r"(c0), "r"(c1), "r"(c2) : "memory");
}
__device__ __forceinline__ void fence_async() { asm volatile("fence.proxy.async.shared::cta;" ::: "memory"); }
template <int ID, int N> __device__ __forceinline__ void bar_sync() { asm volatile("bar.sync %0, %1;" :: "n"(ID), "n"(N) : "memory"); }
template <int ID, int N> __device__ __forceinline__ void bar_arrive() { asm volatile("bar.arrive %0, %1;" :: "n"(ID), "n"(N) : "memory"); }
__device__ __forceinline__ void wg_fence() { asm volatile("wgmma.fence.sync.aligned;" ::: "memory"); }
__device__ __forceinline__ void wg_commit() { asm volatile("wgmma.commit_group.sync.aligned;" ::: "memory"); }
template <int N> __device__ __forceinline__ void wg_wait() { asm volatile("wgmma.wait_group.sync.aligned %0;" :: "n"(N) : "memory"); }
template <int N> __device__ __forceinline__ void pin(float (&d)[N]) {
#pragma unroll
    for (int i = 0; i < N; i++) asm volatile("" : "+f"(d[i]) :: "memory");
}
__host__ __device__ constexpr uint64_t desc(uint32_t addr, uint32_t lbo, uint32_t sbo, uint64_t sw) {
    return (addr >> 4) | ((uint64_t)(lbo >> 4) << 16) | ((uint64_t)(sbo >> 4) << 32) | (sw << 62);
}
__device__ __forceinline__ void ldsm4(uint32_t (&r)[4], uint32_t a) {
    asm volatile("ldmatrix.sync.aligned.m8n8.x4.shared.b16 {%0,%1,%2,%3}, [%4];" : "=r"(r[0]), "=r"(r[1]), "=r"(r[2]), "=r"(r[3]) : "r"(a) : "memory");
}
__device__ __forceinline__ void stsm4(uint32_t a, uint32_t r0, uint32_t r1, uint32_t r2, uint32_t r3) {
    asm volatile("stmatrix.sync.aligned.m8n8.x4.shared.b16 [%0], {%1,%2,%3,%4};" :: "r"(a), "r"(r0), "r"(r1), "r"(r2), "r"(r3) : "memory");
}
__device__ __forceinline__ void stsm2(uint32_t a, uint32_t r0, uint32_t r1) {
    asm volatile("stmatrix.sync.aligned.m8n8.x2.shared.b16 [%0], {%1,%2};" :: "r"(a), "r"(r0), "r"(r1) : "memory");
}
__device__ __forceinline__ void lds128(uint32_t (&r)[4], uint32_t a) {
    asm volatile("ld.shared.v4.b32 {%0,%1,%2,%3}, [%4];" : "=r"(r[0]), "=r"(r[1]), "=r"(r[2]), "=r"(r[3]) : "r"(a) : "memory");
}
__device__ __forceinline__ void sts128(uint32_t a, const uint32_t (&r)[4]) {
    asm volatile("st.shared.v4.b32 [%4], {%0,%1,%2,%3};" :: "r"(r[0]), "r"(r[1]), "r"(r[2]), "r"(r[3]), "r"(a) : "memory");
}
__device__ __forceinline__ void sts32(uint32_t a, uint32_t v) { asm volatile("st.shared.b32 [%0], %1;" :: "r"(a), "r"(v) : "memory"); }
__device__ __forceinline__ uint32_t pack(float lo, float hi) {
    uint32_t r; asm("cvt.rn.bf16x2.f32 %0, %1, %2;" : "=r"(r) : "f"(hi), "f"(lo)); return r;
}
__device__ __forceinline__ uint32_t phi2(float lo, float hi) {
    uint32_t r;
    asm volatile("{ .reg .f32 a, b; .reg .b32 e, t;\n"
        "mul.f32 a, %1, 0f3FB8AA3B; mul.f32 b, %2, 0f3FB8AA3B; ex2.approx.ftz.f32 a, a; ex2.approx.ftz.f32 b, b;\n"
        "cvt.rn.bf16x2.f32 e, b, a; cvt.rn.relu.bf16x2.f32 t, %2, %1;\n"
        "min.NaN.bf16x2 e, e, %3; add.rn.bf16x2 e, e, t; add.rn.bf16x2 %0, e, %4; }"
        : "=r"(r) : "f"(lo), "f"(hi), "r"(0x3F803F80u), "r"(0x35863586u));
    return r;
}
__device__ __forceinline__ float rcp(float t) { float r; asm("rcp.approx.ftz.f32 %0, %1;" : "=f"(r) : "f"(t)); return r; }
template <int OFF> __device__ __forceinline__ void st128(void* p, uint32_t a, uint32_t b, uint32_t c, uint32_t d) {
    asm volatile("{ .reg .b128 v; .reg .b64 lo, hi; mov.b64 lo, {%1,%2}; mov.b64 hi, {%3,%4}; mov.b128 v, {lo,hi};\n"
                 "st.relaxed.gpu.global.b128 [%0 + %5], v; }" :: "l"(p), "r"(a), "r"(b), "r"(c), "r"(d), "n"(OFF) : "memory");
}
template <int OFF> __device__ __forceinline__ void st64(void* p, uint32_t a, uint32_t b) {
    asm volatile("{ .reg .b64 v; mov.b64 v, {%1,%2}; st.relaxed.gpu.global.b64 [%0 + %3], v; }" :: "l"(p), "r"(a), "r"(b), "n"(OFF) : "memory");
}
template <int OFF> __device__ __forceinline__ void ld128(uint32_t (&r)[4], const void* p) {
    asm volatile("{ .reg .b128 v; .reg .b64 lo, hi; ld.relaxed.gpu.global.b128 v, [%4 + %5]; mov.b128 {lo,hi}, v;\n"
                 "mov.b64 {%0,%1}, lo; mov.b64 {%2,%3}, hi; }" : "=r"(r[0]), "=r"(r[1]), "=r"(r[2]), "=r"(r[3]) : "l"(p), "n"(OFF) : "memory");
}
template <int OFF> __device__ __forceinline__ void ld64(uint32_t& a, uint32_t& b, const void* p) {
    asm volatile("{ .reg .b64 v; ld.relaxed.gpu.global.b64 v, [%2 + %3]; mov.b64 {%0,%1}, v; }" : "=r"(a), "=r"(b) : "l"(p), "n"(OFF) : "memory");
}
__device__ __forceinline__ unsigned ld_acq(const unsigned* p) { unsigned v; asm volatile("ld.acquire.gpu.global.u32 %0, [%1];" : "=r"(v) : "l"(p) : "memory"); return v; }
__device__ __forceinline__ unsigned inc_rel(unsigned* p) { unsigned v; asm volatile("atom.release.gpu.global.add.u32 %0, [%1], 1;" : "=r"(v) : "l"(p) : "memory"); return v; }
template <int OFF> __device__ __forceinline__ void red4(void* p, float a, float b, float c, float d) {
    asm volatile("red.relaxed.gpu.global.add.v4.f32 [%0 + %5], {%1,%2,%3,%4};" :: "l"(p), "f"(a), "f"(b), "f"(c), "f"(d), "n"(OFF) : "memory");
}
__device__ __forceinline__ unsigned clk() { unsigned v; asm volatile("mov.u32 %0, %%clock;" : "=r"(v) :: "memory"); return v; }
__device__ __forceinline__ int fresh_tid() { int v; asm volatile("mov.u32 %0, %%tid.x;" : "=r"(v)); return v; }
template <int N> struct Mma;
template <> struct Mma<16> {
    template <int ACC, int OB> static __device__ __forceinline__ void rs(float* d, const uint32_t (&a)[4], uint64_t b) {
        asm volatile("{ .reg .pred p; .reg .b64 db; add.s64 db, %12, %14; setp.ne.b32 p, %13, 0;\n"
            "wgmma.mma_async.sync.aligned.m64n16k16.f32.bf16.bf16 {%0,%1,%2,%3,%4,%5,%6,%7},\n"
            "{%8,%9,%10,%11}, db, p, 1, 1, 1; }"
            : "+f"(d[0]), "+f"(d[1]), "+f"(d[2]), "+f"(d[3]), "+f"(d[4]), "+f"(d[5]), "+f"(d[6]), "+f"(d[7])
            : "r"(a[0]), "r"(a[1]), "r"(a[2]), "r"(a[3]), "l"(b), "n"(ACC), "n"(OB));
    }
    template <int ACC, int OA, int OB, int TA> static __device__ __forceinline__ void ss(float* d, uint64_t a, uint64_t b) {
        asm volatile("{ .reg .pred p; .reg .b64 da, db; add.s64 da, %8, %11; add.s64 db, %9, %12; setp.ne.b32 p, %10, 0;\n"
            "wgmma.mma_async.sync.aligned.m64n16k16.f32.bf16.bf16 {%0,%1,%2,%3,%4,%5,%6,%7},\n"
            "da, db, p, 1, 1, %13, 1; }"
            : "+f"(d[0]), "+f"(d[1]), "+f"(d[2]), "+f"(d[3]), "+f"(d[4]), "+f"(d[5]), "+f"(d[6]), "+f"(d[7])
            : "l"(a), "l"(b), "n"(ACC), "n"(OA), "n"(OB), "n"(TA));
    }
};
template <> struct Mma<24> {
    template <int ACC, int OB> static __device__ __forceinline__ void rs(float* d, const uint32_t (&a)[4], uint64_t b) {
        asm volatile("{ .reg .pred p; .reg .b64 db; add.s64 db, %16, %18; setp.ne.b32 p, %17, 0;\n"
            "wgmma.mma_async.sync.aligned.m64n24k16.f32.bf16.bf16 {%0,%1,%2,%3,%4,%5,%6,%7,%8,%9,%10,%11},\n"
            "{%12,%13,%14,%15}, db, p, 1, 1, 1; }"
            : "+f"(d[0]), "+f"(d[1]), "+f"(d[2]), "+f"(d[3]), "+f"(d[4]), "+f"(d[5]), "+f"(d[6]), "+f"(d[7]), "+f"(d[8]), "+f"(d[9]), "+f"(d[10]), "+f"(d[11])
            : "r"(a[0]), "r"(a[1]), "r"(a[2]), "r"(a[3]), "l"(b), "n"(ACC), "n"(OB));
    }
    template <int ACC, int OA, int OB, int TA> static __device__ __forceinline__ void ss(float* d, uint64_t a, uint64_t b) {
        asm volatile("{ .reg .pred p; .reg .b64 da, db; add.s64 da, %12, %15; add.s64 db, %13, %16; setp.ne.b32 p, %14, 0;\n"
            "wgmma.mma_async.sync.aligned.m64n24k16.f32.bf16.bf16 {%0,%1,%2,%3,%4,%5,%6,%7,%8,%9,%10,%11},\n"
            "da, db, p, 1, 1, %17, 1; }"
            : "+f"(d[0]), "+f"(d[1]), "+f"(d[2]), "+f"(d[3]), "+f"(d[4]), "+f"(d[5]), "+f"(d[6]), "+f"(d[7]), "+f"(d[8]), "+f"(d[9]), "+f"(d[10]), "+f"(d[11])
            : "l"(a), "l"(b), "n"(ACC), "n"(OA), "n"(OB), "n"(TA));
    }
};
template <> struct Mma<32> {
    template <int ACC, int OB> static __device__ __forceinline__ void rs(float* d, const uint32_t (&a)[4], uint64_t b) {
        asm volatile("{ .reg .pred p; .reg .b64 db; add.s64 db, %20, %22; setp.ne.b32 p, %21, 0;\n"
            "wgmma.mma_async.sync.aligned.m64n32k16.f32.bf16.bf16 {%0,%1,%2,%3,%4,%5,%6,%7,%8,%9,%10,%11,%12,%13,%14,%15},\n"
            "{%16,%17,%18,%19}, db, p, 1, 1, 1; }"
            : "+f"(d[0]), "+f"(d[1]), "+f"(d[2]), "+f"(d[3]), "+f"(d[4]), "+f"(d[5]), "+f"(d[6]), "+f"(d[7]), "+f"(d[8]), "+f"(d[9]), "+f"(d[10]), "+f"(d[11]), "+f"(d[12]), "+f"(d[13]), "+f"(d[14]), "+f"(d[15])
            : "r"(a[0]), "r"(a[1]), "r"(a[2]), "r"(a[3]), "l"(b), "n"(ACC), "n"(OB));
    }
    template <int ACC, int OA, int OB, int TA> static __device__ __forceinline__ void ss(float* d, uint64_t a, uint64_t b) {
        asm volatile("{ .reg .pred p; .reg .b64 da, db; add.s64 da, %16, %19; add.s64 db, %17, %20; setp.ne.b32 p, %18, 0;\n"
            "wgmma.mma_async.sync.aligned.m64n32k16.f32.bf16.bf16 {%0,%1,%2,%3,%4,%5,%6,%7,%8,%9,%10,%11,%12,%13,%14,%15},\n"
            "da, db, p, 1, 1, %21, 1; }"
            : "+f"(d[0]), "+f"(d[1]), "+f"(d[2]), "+f"(d[3]), "+f"(d[4]), "+f"(d[5]), "+f"(d[6]), "+f"(d[7]), "+f"(d[8]), "+f"(d[9]), "+f"(d[10]), "+f"(d[11]), "+f"(d[12]), "+f"(d[13]), "+f"(d[14]), "+f"(d[15])
            : "l"(a), "l"(b), "n"(ACC), "n"(OA), "n"(OB), "n"(TA));
    }
};
template <> struct Mma<40> {
    template <int ACC, int OB> static __device__ __forceinline__ void rs(float* d, const uint32_t (&a)[4], uint64_t b) {
        asm volatile("{ .reg .pred p; .reg .b64 db; add.s64 db, %24, %26; setp.ne.b32 p, %25, 0;\n"
            "wgmma.mma_async.sync.aligned.m64n40k16.f32.bf16.bf16 {%0,%1,%2,%3,%4,%5,%6,%7,%8,%9,%10,%11,%12,%13,%14,%15,%16,%17,%18,%19},\n"
            "{%20,%21,%22,%23}, db, p, 1, 1, 1; }"
            : "+f"(d[0]), "+f"(d[1]), "+f"(d[2]), "+f"(d[3]), "+f"(d[4]), "+f"(d[5]), "+f"(d[6]), "+f"(d[7]), "+f"(d[8]), "+f"(d[9]), "+f"(d[10]), "+f"(d[11]), "+f"(d[12]), "+f"(d[13]), "+f"(d[14]), "+f"(d[15]), "+f"(d[16]), "+f"(d[17]), "+f"(d[18]), "+f"(d[19])
            : "r"(a[0]), "r"(a[1]), "r"(a[2]), "r"(a[3]), "l"(b), "n"(ACC), "n"(OB));
    }
    template <int ACC, int OA, int OB, int TA> static __device__ __forceinline__ void ss(float* d, uint64_t a, uint64_t b) {
        asm volatile("{ .reg .pred p; .reg .b64 da, db; add.s64 da, %20, %23; add.s64 db, %21, %24; setp.ne.b32 p, %22, 0;\n"
            "wgmma.mma_async.sync.aligned.m64n40k16.f32.bf16.bf16 {%0,%1,%2,%3,%4,%5,%6,%7,%8,%9,%10,%11,%12,%13,%14,%15,%16,%17,%18,%19},\n"
            "da, db, p, 1, 1, %25, 1; }"
            : "+f"(d[0]), "+f"(d[1]), "+f"(d[2]), "+f"(d[3]), "+f"(d[4]), "+f"(d[5]), "+f"(d[6]), "+f"(d[7]), "+f"(d[8]), "+f"(d[9]), "+f"(d[10]), "+f"(d[11]), "+f"(d[12]), "+f"(d[13]), "+f"(d[14]), "+f"(d[15]), "+f"(d[16]), "+f"(d[17]), "+f"(d[18]), "+f"(d[19])
            : "l"(a), "l"(b), "n"(ACC), "n"(OA), "n"(OB), "n"(TA));
    }
};
template <> struct Mma<48> {
    template <int ACC, int OB> static __device__ __forceinline__ void rs(float* d, const uint32_t (&a)[4], uint64_t b) {
        asm volatile("{ .reg .pred p; .reg .b64 db; add.s64 db, %28, %30; setp.ne.b32 p, %29, 0;\n"
            "wgmma.mma_async.sync.aligned.m64n48k16.f32.bf16.bf16 {%0,%1,%2,%3,%4,%5,%6,%7,%8,%9,%10,%11,%12,%13,%14,%15,%16,%17,%18,%19,%20,%21,%22,%23},\n"
            "{%24,%25,%26,%27}, db, p, 1, 1, 1; }"
            : "+f"(d[0]), "+f"(d[1]), "+f"(d[2]), "+f"(d[3]), "+f"(d[4]), "+f"(d[5]), "+f"(d[6]), "+f"(d[7]), "+f"(d[8]), "+f"(d[9]), "+f"(d[10]), "+f"(d[11]), "+f"(d[12]), "+f"(d[13]), "+f"(d[14]), "+f"(d[15]), "+f"(d[16]), "+f"(d[17]), "+f"(d[18]), "+f"(d[19]), "+f"(d[20]), "+f"(d[21]), "+f"(d[22]), "+f"(d[23])
            : "r"(a[0]), "r"(a[1]), "r"(a[2]), "r"(a[3]), "l"(b), "n"(ACC), "n"(OB));
    }
    template <int ACC, int OA, int OB, int TA> static __device__ __forceinline__ void ss(float* d, uint64_t a, uint64_t b) {
        asm volatile("{ .reg .pred p; .reg .b64 da, db; add.s64 da, %24, %27; add.s64 db, %25, %28; setp.ne.b32 p, %26, 0;\n"
            "wgmma.mma_async.sync.aligned.m64n48k16.f32.bf16.bf16 {%0,%1,%2,%3,%4,%5,%6,%7,%8,%9,%10,%11,%12,%13,%14,%15,%16,%17,%18,%19,%20,%21,%22,%23},\n"
            "da, db, p, 1, 1, %29, 1; }"
            : "+f"(d[0]), "+f"(d[1]), "+f"(d[2]), "+f"(d[3]), "+f"(d[4]), "+f"(d[5]), "+f"(d[6]), "+f"(d[7]), "+f"(d[8]), "+f"(d[9]), "+f"(d[10]), "+f"(d[11]), "+f"(d[12]), "+f"(d[13]), "+f"(d[14]), "+f"(d[15]), "+f"(d[16]), "+f"(d[17]), "+f"(d[18]), "+f"(d[19]), "+f"(d[20]), "+f"(d[21]), "+f"(d[22]), "+f"(d[23])
            : "l"(a), "l"(b), "n"(ACC), "n"(OA), "n"(OB), "n"(TA));
    }
};
template <> struct Mma<56> {
    template <int ACC, int OB> static __device__ __forceinline__ void rs(float* d, const uint32_t (&a)[4], uint64_t b) {
        asm volatile("{ .reg .pred p; .reg .b64 db; add.s64 db, %32, %34; setp.ne.b32 p, %33, 0;\n"
            "wgmma.mma_async.sync.aligned.m64n56k16.f32.bf16.bf16 {%0,%1,%2,%3,%4,%5,%6,%7,%8,%9,%10,%11,%12,%13,%14,%15,%16,%17,%18,%19,%20,%21,%22,%23,%24,%25,%26,%27},\n"
            "{%28,%29,%30,%31}, db, p, 1, 1, 1; }"
            : "+f"(d[0]), "+f"(d[1]), "+f"(d[2]), "+f"(d[3]), "+f"(d[4]), "+f"(d[5]), "+f"(d[6]), "+f"(d[7]), "+f"(d[8]), "+f"(d[9]), "+f"(d[10]), "+f"(d[11]), "+f"(d[12]), "+f"(d[13]), "+f"(d[14]), "+f"(d[15]), "+f"(d[16]), "+f"(d[17]), "+f"(d[18]), "+f"(d[19]), "+f"(d[20]), "+f"(d[21]), "+f"(d[22]), "+f"(d[23]), "+f"(d[24]), "+f"(d[25]), "+f"(d[26]), "+f"(d[27])
            : "r"(a[0]), "r"(a[1]), "r"(a[2]), "r"(a[3]), "l"(b), "n"(ACC), "n"(OB));
    }
    template <int ACC, int OA, int OB, int TA> static __device__ __forceinline__ void ss(float* d, uint64_t a, uint64_t b) {
        asm volatile("{ .reg .pred p; .reg .b64 da, db; add.s64 da, %28, %31; add.s64 db, %29, %32; setp.ne.b32 p, %30, 0;\n"
            "wgmma.mma_async.sync.aligned.m64n56k16.f32.bf16.bf16 {%0,%1,%2,%3,%4,%5,%6,%7,%8,%9,%10,%11,%12,%13,%14,%15,%16,%17,%18,%19,%20,%21,%22,%23,%24,%25,%26,%27},\n"
            "da, db, p, 1, 1, %33, 1; }"
            : "+f"(d[0]), "+f"(d[1]), "+f"(d[2]), "+f"(d[3]), "+f"(d[4]), "+f"(d[5]), "+f"(d[6]), "+f"(d[7]), "+f"(d[8]), "+f"(d[9]), "+f"(d[10]), "+f"(d[11]), "+f"(d[12]), "+f"(d[13]), "+f"(d[14]), "+f"(d[15]), "+f"(d[16]), "+f"(d[17]), "+f"(d[18]), "+f"(d[19]), "+f"(d[20]), "+f"(d[21]), "+f"(d[22]), "+f"(d[23]), "+f"(d[24]), "+f"(d[25]), "+f"(d[26]), "+f"(d[27])
            : "l"(a), "l"(b), "n"(ACC), "n"(OA), "n"(OB), "n"(TA));
    }
};
template <> struct Mma<72> {
    template <int ACC, int OB> static __device__ __forceinline__ void rs(float* d, const uint32_t (&a)[4], uint64_t b) {
        asm volatile("{ .reg .pred p; .reg .b64 db; add.s64 db, %40, %42; setp.ne.b32 p, %41, 0;\n"
            "wgmma.mma_async.sync.aligned.m64n72k16.f32.bf16.bf16 {%0,%1,%2,%3,%4,%5,%6,%7,%8,%9,%10,%11,%12,%13,%14,%15,%16,%17,%18,%19,%20,%21,%22,%23,%24,%25,%26,%27,%28,%29,%30,%31,%32,%33,%34,%35},\n"
            "{%36,%37,%38,%39}, db, p, 1, 1, 1; }"
            : "+f"(d[0]), "+f"(d[1]), "+f"(d[2]), "+f"(d[3]), "+f"(d[4]), "+f"(d[5]), "+f"(d[6]), "+f"(d[7]), "+f"(d[8]), "+f"(d[9]), "+f"(d[10]), "+f"(d[11]), "+f"(d[12]), "+f"(d[13]), "+f"(d[14]), "+f"(d[15]), "+f"(d[16]), "+f"(d[17]), "+f"(d[18]), "+f"(d[19]), "+f"(d[20]), "+f"(d[21]), "+f"(d[22]), "+f"(d[23]), "+f"(d[24]), "+f"(d[25]), "+f"(d[26]), "+f"(d[27]), "+f"(d[28]), "+f"(d[29]), "+f"(d[30]), "+f"(d[31]), "+f"(d[32]), "+f"(d[33]), "+f"(d[34]), "+f"(d[35])
            : "r"(a[0]), "r"(a[1]), "r"(a[2]), "r"(a[3]), "l"(b), "n"(ACC), "n"(OB));
    }
    template <int ACC, int OA, int OB, int TA> static __device__ __forceinline__ void ss(float* d, uint64_t a, uint64_t b) {
        asm volatile("{ .reg .pred p; .reg .b64 da, db; add.s64 da, %36, %39; add.s64 db, %37, %40; setp.ne.b32 p, %38, 0;\n"
            "wgmma.mma_async.sync.aligned.m64n72k16.f32.bf16.bf16 {%0,%1,%2,%3,%4,%5,%6,%7,%8,%9,%10,%11,%12,%13,%14,%15,%16,%17,%18,%19,%20,%21,%22,%23,%24,%25,%26,%27,%28,%29,%30,%31,%32,%33,%34,%35},\n"
            "da, db, p, 1, 1, %41, 1; }"
            : "+f"(d[0]), "+f"(d[1]), "+f"(d[2]), "+f"(d[3]), "+f"(d[4]), "+f"(d[5]), "+f"(d[6]), "+f"(d[7]), "+f"(d[8]), "+f"(d[9]), "+f"(d[10]), "+f"(d[11]), "+f"(d[12]), "+f"(d[13]), "+f"(d[14]), "+f"(d[15]), "+f"(d[16]), "+f"(d[17]), "+f"(d[18]), "+f"(d[19]), "+f"(d[20]), "+f"(d[21]), "+f"(d[22]), "+f"(d[23]), "+f"(d[24]), "+f"(d[25]), "+f"(d[26]), "+f"(d[27]), "+f"(d[28]), "+f"(d[29]), "+f"(d[30]), "+f"(d[31]), "+f"(d[32]), "+f"(d[33]), "+f"(d[34]), "+f"(d[35])
            : "l"(a), "l"(b), "n"(ACC), "n"(OA), "n"(OB), "n"(TA));
    }
};
template <> struct Mma<144> {
    template <int ACC, int OB> static __device__ __forceinline__ void rs(float* d, const uint32_t (&a)[4], uint64_t b) {
        asm volatile("{ .reg .pred p; .reg .b64 db; add.s64 db, %76, %78; setp.ne.b32 p, %77, 0;\n"
            "wgmma.mma_async.sync.aligned.m64n144k16.f32.bf16.bf16 {%0,%1,%2,%3,%4,%5,%6,%7,%8,%9,%10,%11,%12,%13,%14,%15,%16,%17,%18,%19,%20,%21,%22,%23,%24,%25,%26,%27,%28,%29,%30,%31,%32,%33,%34,%35,%36,%37,%38,%39,%40,%41,%42,%43,%44,%45,%46,%47,%48,%49,%50,%51,%52,%53,%54,%55,%56,%57,%58,%59,%60,%61,%62,%63,%64,%65,%66,%67,%68,%69,%70,%71},\n"
            "{%72,%73,%74,%75}, db, p, 1, 1, 1; }"
            : "+f"(d[0]), "+f"(d[1]), "+f"(d[2]), "+f"(d[3]), "+f"(d[4]), "+f"(d[5]), "+f"(d[6]), "+f"(d[7]), "+f"(d[8]), "+f"(d[9]), "+f"(d[10]), "+f"(d[11]), "+f"(d[12]), "+f"(d[13]), "+f"(d[14]), "+f"(d[15]), "+f"(d[16]), "+f"(d[17]), "+f"(d[18]), "+f"(d[19]), "+f"(d[20]), "+f"(d[21]), "+f"(d[22]), "+f"(d[23]), "+f"(d[24]), "+f"(d[25]), "+f"(d[26]), "+f"(d[27]), "+f"(d[28]), "+f"(d[29]), "+f"(d[30]), "+f"(d[31]), "+f"(d[32]), "+f"(d[33]), "+f"(d[34]), "+f"(d[35]), "+f"(d[36]), "+f"(d[37]), "+f"(d[38]), "+f"(d[39]), "+f"(d[40]), "+f"(d[41]), "+f"(d[42]), "+f"(d[43]), "+f"(d[44]), "+f"(d[45]), "+f"(d[46]), "+f"(d[47]), "+f"(d[48]), "+f"(d[49]), "+f"(d[50]), "+f"(d[51]), "+f"(d[52]), "+f"(d[53]), "+f"(d[54]), "+f"(d[55]), "+f"(d[56]), "+f"(d[57]), "+f"(d[58]), "+f"(d[59]), "+f"(d[60]), "+f"(d[61]), "+f"(d[62]), "+f"(d[63]), "+f"(d[64]), "+f"(d[65]), "+f"(d[66]), "+f"(d[67]), "+f"(d[68]), "+f"(d[69]), "+f"(d[70]), "+f"(d[71])
            : "r"(a[0]), "r"(a[1]), "r"(a[2]), "r"(a[3]), "l"(b), "n"(ACC), "n"(OB));
    }
};

template <int I, int N, class F> __device__ __forceinline__ void static_for(F&& f) {
    if constexpr (I < N) { f(std::integral_constant<int, I>{}); static_for<I + 1, N>(f); }
}
#define SFOR(var, lo, hi) static_for<lo, hi>([&](auto var##_c) { constexpr int var = decltype(var##_c)::value;
#define SEND });
template <int N> constexpr std::integral_constant<int, N> IC{};

struct Zeros { uint64_t z[1]; uint64_t d[4][2][4][3]; };
struct Maps { CUtensorMap x, w, w16, wo, wot, out, outt; };
constexpr uint32_t sb = 1024, bars = sb + OFF_BAR;

__device__ __forceinline__ void load_kv(uint32_t (&s)[8][4], const void* p) { SFOR(u, 0, 8) ld128<u * 1536>(s[u], p); SEND }

template <int V>
__device__ __forceinline__ void front(uint32_t (&pq)[5][4], uint32_t (&ks)[8][4], Scratch* sc, int g, int hh, int w, int q, bool lead, const Zeros& zs) {
    const uint64_t dz = zs.z[0];
    constexpr int NB = 64 - 8 * V, NS = 8 + 8 * V;
    const int lane = threadIdx.x & 31, c = lane & 3, half = hh ^ w;
    const uint32_t xo = sb + (half * 64 + q * 16 + (lane & 15)) * 128, xs = ((lane >> 4) ^ (lane & 7)) << 4;
    const uint64_t dx = dz + desc(sb, 16, 1024, 1) + half * 512;
    uint64_t dm, dt, dn;
    auto rebase = [&](int i) { dm = zs.d[V][hh][i][0]; dt = zs.d[V][hh][i][1]; dn = zs.d[V][hh][i][2]; };
    uint32_t xa[36][4];
    auto mma = [&](auto N, auto A, auto OX, auto OB, float* d, const uint32_t (&a)[4], uint64_t db) {
        if constexpr (OX.value < 0) Mma<N.value>::template rs<A.value, OB.value>(d, a, db);
        else Mma<N.value>::template ss<A.value, OX.value / 16, OB.value, 0>(d, dx, db);
    };
    auto step = [&](auto A, auto OX, auto OM, auto OO, float* d, const uint32_t (&a)[4]) {
        if constexpr (V == 0) mma(IC<72>, A, OX, IC<OM.value / 16 + (OO.value - OM.value) * 4096>, d, a, dm);
        else { mma(IC<NB>, A, OX, IC<OM.value / 16>, d, a, dm); mma(IC<NS>, A, OX, IC<OO.value / 16>, d + NB / 2, a, dt); }
    };
    float aq[36];
    auto q_steps = [&](auto LO, auto HI) {
        SFOR(i, LO.value, HI.value)
            constexpr int j = i / 4, s = i & 3;
            if (i % 12 == 0) { mbar_wait(bars + 8 * (B_FULL + 12 + i / 12)); wg_fence(); }
            step(IC<(i > 0)>, IC<-1>, IC<tile_q(j) + s * 2048>, IC<tile_q(j) + 8192 + s * 2048>, aq, xa[i]);
            if (i == Q_GO && !w) bar_arrive<2, 256>();
            if (s == 1 && j > 0 && j % 3 != 1) {
                wg_commit();
                wg_wait<1>();
                if (lead) mbar_arrive(bars + 8 * (B_EMP + 12 + (2 * j) / 3));
            }
            if ((s == 3 && j % 3 != 0) || i == HI.value - 1) wg_commit();
        SEND
    };
    {
        float acc[72], kp[20];
        const int kg = w * 8 + q * 2 + ((lane >> 3) & 1), hi = lane >> 4;
        uint32_t pk[4];
        SFOR(st, 0, 12)
            if (st % 4 == 0) rebase(st / 4);
            mbar_wait(bars + 8 * (st ? B_FULL + st : B_F0));
            if (st == 0) { STAMPW(4 + w); SFOR(s, 0, 4) ldsm4(xa[s], xo + slot_x(0) + (xs ^ (32 * s))); SEND }
            wg_fence();
            SFOR(s, 0, 4)
                constexpr int ik = 4 * st + s, iv = st >= 9 ? ik - 12 : st > 0 && s < 3 ? 3 * st - 3 + s : -1;
                constexpr int OK = slot(TAB_K, st) + s * 2048, OV = slot(TAB_V, iv / 4 + 3) + (iv & 3) * 2048;
                constexpr int OX = slot_x(8) + 96;
                if constexpr (st < 9) {
                    if constexpr (V == 1) {
                        mma(IC<56>, IC<(ik > 0)>, IC<(ik == 35 ? OX : -1)>, IC<OK / 16>, acc, xa[ik], dm);
                        mma(IC<32>, IC<(ik > 0)>, IC<(ik == 35 ? OX : -1)>, IC<(slot(TAB_K, st) + 8192 + s * 512) / 16>, acc + 28, xa[ik], dn);
                    } else step(IC<(ik > 0)>, IC<(ik == 35 ? OX : -1)>, IC<OK>, IC<OK + 8192>, acc, xa[ik]);
                }
                if constexpr (iv >= 0) {
                    if constexpr (V == 1) mma(IC<56>, IC<(iv > 0)>, IC<(iv == 35 ? OX : -1)>, IC<OV / 16>, acc + 44, xa[iv], dm);
                    else step(IC<(iv > 0)>, IC<(iv == 35 ? OX : -1)>, IC<OV>, IC<OV + 8192>, acc + 36, xa[iv]);
                }
                if (s == 0 && st > 0) {
                    wg_commit();
                    wg_wait<1>();
                    if (lead) mbar_arrive(bars + 8 * (B_EMP + st - 1) + (st < 8 ? (xa[4 * st + 1][0] | xa[4 * st + 2][0] | xa[4 * st + 3][0]) & (uint32_t)dz : 0));
                }
                if (s == (st ? 0 : 3) && st < 8) {
                    if (st == 0) { wg_commit(); mbar_wait(bars + 8 * B_FULL); }
                    SFOR(i, 0, 4) if constexpr (4 * st + 4 + i < 35) ldsm4(xa[4 * st + 4 + i], xo + slot_x(st + 1) + (xs ^ (32 * i))); SEND
                    if (st) wg_fence();
                }
                if constexpr (st >= 9) {
                    constexpr int i = ik - 36;
                    if (i == 0) {
                        STAMPW(2 + w);
#pragma unroll
                        for (int j = 0; j < 36; j++) asm volatile("" : "+f"(acc[j]) :: "memory");
                        mbar_wait(bars + 8 * (B_EMP + 7));
                    }
                    if (i == 11) wg_commit();
                    SFOR(j, (3 * i + 1) / 2, (3 * i + 4) / 2)
                        pk[j & 3] = phi2(acc[2 * j], acc[2 * j + 1]);
                        const uint32_t pb = sb + OFF_PK + kg * 1152 + (lane & 7) * 16 + hi * 128;
                        const uint32_t pm = pb + hh * NS * 16, pt = pb - hh * NB * 16;
                        if ((j & 3) == 3) stsm4((4 * j - 4 < NB ? pm : 4 * j - 4 > NB ? pt : hi ? pt : pm) + (j / 4) * 256, pk[0], pk[1], pk[2], pk[3]);
                        if (j == 17) stsm2(pt + 1024, pk[0], pk[1]);
                    SEND
                }
            SEND
            if (st > 0 && st < 11) wg_commit();
        SEND
        rebase(3);
        q_steps(IC<0>, IC<Q_A>);
        mbar_wait(bars + 8 * (B_EMP + 10));
        wg_wait<(Q_A > 0)>();
#pragma unroll
        for (int j = 36; j < 72; j++) asm volatile("" : "+f"(acc[j]) :: "memory");
        if (lead) mbar_arrive(bars + 8 * (B_EMP + 11));
        STAMPW(6 + w);
        {
            const uint32_t vb = sb + OFF_V + kg * 1280 + (lane & 7) * 16 + hi * 128;
            uint32_t t[18], v[18];
#pragma unroll
            for (int i = 0; i < 18; i++) { const float* a = acc + 36 + (V == 1 ? (2 * i + 8) % 36 : 2 * i); t[i] = pack(a[0], a[1]); }
#pragma unroll
            for (int i = 0; i < 18; i++) v[i] = hh ? t[(i + NB / 4) % 18] : t[i];
            const uint32_t one = 0x3F803F80u;
            stsm4(vb + 512, c < 2 ? v[8] : one, c < 2 ? v[9] : one, c < 2 ? one : v[8], c < 2 ? one : v[9]);
#pragma unroll
            for (int i = 0; i < 4; i++) { const uint32_t* a = v + 4 * i + (i >> 1) * 2; stsm4(vb + (2 * i + (i >> 1) * 2) * 128, a[0], a[1], a[2], a[3]); }
        }
        ldsm4(xa[35], xo + slot_x(8) + (xs ^ 96));
        const uint32_t dep = xa[35][0];
        fence_async();
        bar_sync<1, 256>();
        STAMPW(8 + w);
        const uint64_t da = dz + desc(sb + OFF_PK, 1152, 128, 0) + w * 32, db = dz + desc(sb + OFF_V, 1280, 128, 0) + w * 40;
        wg_fence();
        SFOR(s, 0, 8) Mma<40>::ss<(s > 0), s * 144, s * 160, 1>(kp, da, db); SEND
        wg_commit();
        uint32_t km[2];
#pragma unroll
        for (int e = 0; e < 2; e++) {
            const uint32_t mm = q * 16 + (lane >> 2) + 8 * e - 4 * w;
            km[e] = (mm < 18 ? (w ? 0x030F0D0Du : 0x2727230Fu) : (w ? 0x7F6C6E6Eu : 0x7B7B7F7Cu)) >> (8 * c);
            if (mm >= 36) km[e] = 0u;
            asm volatile("" : "+r"(km[e]));
        }
        mbar_wait(bars + 8 * B_INIT);
        wg_fence();
        q_steps(IC<Q_A>, IC<Q_B>);
        wg_wait<(Q_B > Q_A)>();
        pin(kp);
        {
            char* const dst = (char*)(sc->kv + (g * 2 + w) * 384 + q * 32 + lane);
            SFOR(o, 0, 4)
                const uint32_t k = km[o >> 1];
                if (k) red4<o * 1536>(dst, k & (1 << (o & 1)) ? (k & 16 ? kp[8 + o] : kp[o]) : 0.f, k & 64 ? kp[12 + o] : kp[4 + o],
                                      k & (4 << (o & 1)) ? (k & 32 ? kp[16 + o] : kp[8 + o]) : 0.f, 1.f);
            SEND
        }
        if (lead) mbar_arrive(bars + 8 * (B_EMP + 12) + (dep & (uint32_t)dz));
        STAMPW(10 + w);
    }
    if (w) bar_sync<2, 256>();
    wg_fence();
    q_steps(IC<Q_B>, IC<36>);
    wg_wait<0>();
    pin(aq);
    if (lead) mbar_arrive(bars + 8 * (B_EMP + 18));
    STAMPW(12 + w);
    uint32_t t[18];
#pragma unroll
    for (int i = 0; i < 18; i++) {
        if (i == KV_AT && !w && q < 3) load_kv(ks, sc->kv + g * 768 + q * 32 + lane);
        t[i] = phi2(aq[2 * i], aq[2 * i + 1]);
    }
#pragma unroll
    for (int i = 0; i < 18; i++) pq[i >> 2][i & 3] = hh ? t[(i + NB / 4) % 18] : t[i];
}

template <int I, int G> __device__ __forceinline__ void load_o1(uint32_t (&a)[9][4], uint64_t p16, uint64_t p8) {
    if constexpr (I < 8) ld128<(I & 3) * 16384 + (G + I / 4) * 2048>(a[I], (const void*)p16);
    else ld64<(G + I - 8) * 1024>(a[8][2 * (I - 8)], a[8][2 * (I - 8) + 1], (const void*)p8);
}
template <int B> __device__ __forceinline__ void load_o(uint32_t (&a)[9][4], uint64_t p16, uint64_t p8) {
    SFOR(i, 0, 10) if constexpr (B > 0 || (i >= 4 && i != 8)) load_o1<i, (B == 0 ? -1 : B == 3 ? 2 : 0)>(a, p16, p8); SEND
}
template <int B> __device__ __forceinline__ uint32_t max_o(const uint32_t (&a)[9][4]) {
    uint32_t m = a[8][2];
#pragma unroll
    for (int i = B ? 0 : 4; i < (B ? 9 : 8); i++) m = max(m, a[i][0]);
    return m;
}

__global__ void __launch_bounds__(384, 1)
lab_kernel(Scratch* __restrict__ sc, const __grid_constant__ Zeros zs, const __grid_constant__ Maps mp) {
    CLK(c_entry);
    const int tid = threadIdx.x, lane = tid & 31;
    const int hh = blockIdx.z & 1;
    const int r = (blockIdx.z >> 1) * 4 + blockIdx.x;
    const int g = hh ? 7 - blockIdx.y : blockIdx.y;
    const int cb = g & 3;
    const int bid = r * 8 + g;

    const int lm = (g + hh) * 64, lo = (g + 1 - hh) * 64;
    const bool narrow = blockIdx.y == 1;
    const CUtensorMap* const mko = narrow ? &mp.w16 : &mp.w;
    const int cko = narrow ? (hh ? 432 : 128) : 576 + lo;
    const uint32_t bk = narrow ? 12288 : 16384, bv = narrow ? 8192 : 16384;
    const int warp = __shfl_sync(0xffffffffu, tid >> 5, 0);
    if (warp >= 8) {
        asm volatile("setmaxnreg.dec.sync.aligned.u32 24;");
        if (warp == 8) {
            CLK(c_a);
            const bool lead = elect();
            if (lead) {
#pragma unroll
                for (int i = 0; i < 8; i++) mbar_init(bars + 8 * i, 1);
            }
            CLK(c_b);
            if (lead) tma4(sb + slot_x(0), &mp.x, 0, r * 128, 0, 0, bars + 8 * B_F0);
            CLK(c_c);
            PUT(96, c_entry); PUT(40, c_a); PUT(41, c_b); PUT(42, c_c);
            bar_arrive<0, 352>();
            uint32_t tk = TAB_K, tx = TAB_X, b = bars + 8 * B_F0;
#pragma unroll 1
            for (int s = 0; s < 9; s++) {
                const uint32_t uk = sb + (tk & 255) * 1024, ux = sb + (tx & 255) * 1024, bx = bars + 8 * (B_FULL + s);
                if (s >= 4) mbar_wait(bx + 8 * (B_EMP - 4 - B_FULL));
                if (lead) {
                    tma4(uk, &mp.w, 576 + lm, 0, 0, s, b);
                    tma4(uk + 8192, mko, cko, 0, narrow, s, b);
                }
                if (s == 8) break;
                if (lead) tma4(ux, &mp.x, 0, r * 128, 0, s + 1, bx);
                STAMPW(80 + s);
                if (s == 2) bar_sync<5, 288>();
                if (s < 3) bar_sync<6, 64>();
                tk = __funnelshift_r(tk, tk, 8); tx = __funnelshift_r(tx, tx, 8);
                b = bx + 8;
            }
#pragma unroll 1
            for (int j = 0; j < 9; j++) {
                const uint32_t u = sb + tile_q(j), bq = bars + 8 * (B_FULL + 12) + ((j * 11) >> 5) * 8;
                mbar_wait(bars + 8 * (B_EMP + min(j + 4, 11)));
                if (lead) {
                    tma4(u, &mp.w, lm, 0, 0, j, bq);
                    tma4(u + 8192, &mp.w, lo, 0, 0, j, bq);
                }
            }
        } else if (warp == 10) {
            const bool lead = elect();
            bar_arrive<0, 352>();
            uint32_t tv = TAB_V >> 24 | TAB_V << 8;
#pragma unroll 1
            for (int c = 0; c < 9; c++) {
                const uint32_t u = sb + (tv & 255) * 1024, b = bars + 8 * (B_FULL + 1 + c) + ((c * 11) >> 5) * 8;
                if (c >= 3) mbar_wait(bars + 8 * B_EMP + ((0x764320u >> (4 * c - 12)) & 7) * 8);
                else bar_sync<6, 64>();
                if (lead) tma4(u, &mp.w, 1152 + lm, 0, 0, c, b);
                if (!narrow) { if (lead) tma4(u + 8192, &mp.w, 1152 + lo, 0, 0, c, b); }
                if (c >= 5) STAMPW(83 + c);
                tv = __funnelshift_r(tv, tv, 8);
            }
#pragma unroll 1
            for (int p = 0; p < 8; p++) {
                const uint32_t u = sb + tile_o(p), b = bars + 8 * (B_FULL + 15 + min(p >> 1, 2));
                const int gp = (g & (p < 2 ? 7 : p < 4 ? 6 : 4)) ^ p;
                mbar_wait(bars + 8 * (B_EMP + max(p + 11, 12)));
                if (lead) {
                    tma4(u, &mp.wo, 0, 0, cb * 2, gp, b);
                    tma4(u + 18432, &mp.wot, 512 + cb * 16, 0, 0, gp, b);
                }
                STAMP(64 + p);
            }
            if (lane == 0) { DUMP(40, 92, 1); }
        } else if (warp == 9) {
            bar_sync<0, 352>();
            if (lane < 19) mbar_expect(bars + 8 * lane, lane == 1 ? 16384 : lane < 13 ? (lane < 10 ? bk : 0) + ((lane & 3) != 1 && lane ? bv : 0) + (lane < 9 ? 16384 : 0) : lane < 16 ? 49152 : lane < 18 ? 41472 : 82944);
            GT(0);
#pragma unroll 1
            for (int i = lane; i < 48; i += 32) {
                const uint32_t t = (r & 1) * 48 + i, mm = (t >> 5) * 16 + ((t & 31) >> 2) + (r & 4) * 2 - (r >> 3) * 4;
                st128<0>(sc->kv + g * 768 + r * 48 + i, 0u, 0u, 0u, mm < 36 ? 0u : 0x41800000u);
            }
#pragma unroll 1
            for (int i = lane; i < 1152; i += 32) {
                st128<0>(sc->o + bid * 1152 + i, SENT, SENT, SENT, SENT);
                if (i < 480) sts128(sb + OFF_BKV + i * 16, {0u, 0u, 0u, 0u});
            }
            STAMPW(43);
            fence_async();
            __syncwarp();
            if (elect()) {
                const unsigned all = (inc_rel(&sc->init) | 127u) + 1u;
                STAMPW(44);
#pragma unroll 1
                for (int n = 0; n < SPIN_LIMIT && (int)(ld_acq(&sc->init) - all) < 0; n++) {}
                mbar_arrive(bars + 8 * B_INIT);
                STAMPW(46);
            }
        }
    } else {
        const bool lead = elect();
        if (lead) {
#pragma unroll
            for (int i = 0; i < 8; i++) mbar_init(bars + 64 * (warp + 1) + 8 * i, warp < 2 ? 1 : 8);
        }
        bar_arrive<5, 288>();
        bar_sync<0, 352>();
        asm volatile("setmaxnreg.inc.sync.aligned.u32 240;");
        const int w = warp >> 2, q = warp & 3, t = tid & 127;
        const int half = hh ^ w;
        const int c = lane & 3;
        STAMPW(0 + w);
        const uint64_t dz = zs.z[0];
        uint32_t pq[5][4], s[8][4];
        switch (blockIdx.y) {
            case 0: front<0>(pq, s, sc, g, hh, w, q, lead, zs); break;
            case 1: front<1>(pq, s, sc, g, hh, w, q, lead, zs); break;
            case 2: front<2>(pq, s, sc, g, hh, w, q, lead, zs); break;
            default: front<3>(pq, s, sc, g, hh, w, q, lead, zs); break;
        }
        pq[4][2] = pq[4][3] = 0u;
#pragma unroll
        for (int i = 0; i < 20; i++) asm volatile("" : "+r"(pq[i >> 2][i & 3]));
        STAMPW(14 + w);
        const int t2 = fresh_tid() & 127;
        if (w == 0) {
            if (q < 3) {
#pragma unroll 1
                for (int n = 0; n < SPIN_LIMIT; n++) {
                    uint32_t m = 0x41800000u;
#pragma unroll
                    for (int u = 0; u < 8; u++) m = min(m, s[u][3]);
                    if (__all_sync(0xffffffffu, m == 0x41800000u)) break;
                    load_kv(s, sc->kv + g * 768 + t2);
                }
                STAMPW(16);
                const uint32_t bb = sb + OFF_BKV + q * 1152 + t2 * 4;
#pragma unroll
                for (int p = 0; p < 2; p++) {
#pragma unroll
                    for (int e = 0; e < 2; e++) {
                        const bool isB = q * 16 + (lane >> 2) + 8 * e - 4 * p >= 18;
                        const uint32_t a0 = bb + p * 3840 + e * 640, a1 = isB ? a0 + 256 : a0;
                        const uint32_t(&a)[4] = s[4 * p + 2 * e];
                        const uint32_t(&b)[4] = s[4 * p + 2 * e + 1];
                        sts32(p && c != 3 ? a0 : a1, pack(__uint_as_float(a[0]), __uint_as_float(b[0])));
                        sts32(a1 + 128, pack(__uint_as_float(a[1]), __uint_as_float(b[1])));
                        sts32(!p && c != 0 ? a0 + 512 : a1 + 256, pack(__uint_as_float(a[2]), __uint_as_float(b[2])));
                    }
                }
                fence_async();
            }
            bar_arrive<4, 256>();
            bar_sync<3, 128>();
        } else {
            bar_sync<4, 256>();
        }
        STAMPW(18 + w);
        uint32_t oa[4][9][4];
        const uint64_t p16 = (uint64_t)(sc->o + ((r * 2 + half) * 32 + g) * 128 + t2), p8 = (uint64_t)(sc->oh + ((r * 2 + half) * 8 + g) * 128 + t2);
        {
            float nx[20], ny[20];
            const uint64_t db = dz + desc(sb + OFF_BKV, 640, 128, 0);
            wg_fence();
            SFOR(s, 0, 3)
                Mma<40>::rs<(s > 0), s * 80>(nx, pq[s], db);
                Mma<40>::rs<(s > 0), 240 + s * 80>(ny, pq[2 + s], db);
            SEND
            wg_commit();
            wg_wait<0>();
            pin(nx); pin(ny);
#pragma unroll
            for (int e = 0; e < 2; e++) {
                const float ma = rcp((c < 2 ? ny[2 * e] : nx[16 + 2 * e]) + 1e-6f);
                const float mb = rcp((c < 2 ? ny[2 * e + 1] : nx[17 + 2 * e]) + 1e-6f);
                const float ta = __shfl_xor_sync(0xffffffffu, ma, 2), tb = __shfl_xor_sync(0xffffffffu, mb, 2);
                const float r0 = c < 2 ? ta : ma, r1 = c < 2 ? tb : mb, r2 = c < 2 ? ma : ta, r3 = c < 2 ? mb : tb;
                const float r01 = c == 0 ? r0 : r1, r23 = c == 3 ? r3 : r2, r12 = c < 2 ? tb : ta;
                const int z = 2 * e;
                oa[0][0][0 + e] = pack(nx[z] * r0, nx[z + 1] * r0);
                oa[0][0][2 + e] = pack(nx[4 + z] * r0, nx[5 + z] * r0);
                oa[0][1][0 + e] = pack(nx[8 + z] * r01, nx[9 + z] * r01);
                oa[0][1][2 + e] = pack(nx[12 + z] * r1, nx[13 + z] * r1);
                oa[0][2][0 + e] = pack((c < 2 ? nx[16 + z] : ny[z]) * r12, (c < 2 ? nx[17 + z] : ny[z + 1]) * r12);
                oa[0][2][2 + e] = pack(ny[4 + z] * r2, ny[5 + z] * r2);
                oa[0][3][0 + e] = pack(ny[8 + z] * r23, ny[9 + z] * r23);
                oa[0][3][2 + e] = pack(ny[12 + z] * r3, ny[13 + z] * r3);
                oa[0][8][e] = pack(ny[16 + z] * r3, ny[17 + z] * r3);
            }
            if (w) bar_sync<1, 256>();
            SFOR(i, 0, 4) st128<i * 16384>((void*)p16, oa[0][i][0], oa[0][i][1], oa[0][i][2], oa[0][i][3]); SEND
            st64<0>((void*)p8, oa[0][8][0], oa[0][8][1]);
        }
        STAMPW(20 + w);
        if (w) {
            const unsigned c0 = clk();
            while (clk() - c0 < DELAY_LATE) {}
            bar_arrive<2, 256>();
        } else {
            bar_arrive<1, 256>();
            const unsigned c0 = clk();
            float ao[72];
            const uint64_t db = dz + desc(sb, 9216, 1024, 1), dp = dz + desc(sb, 9216, 27648, 1);
            mbar_wait(bars + 8 * (B_FULL + 15));
            wg_fence();
            SFOR(i, 0, 4) Mma<144>::rs<(i > 0), i * 128>(ao, oa[0][i], db); SEND
            wg_commit();
            wg_wait<0>();
            const uint64_t q16[3] = {p16 ^ 2048, (p16 ^ 4096) & ~2048ull, (p16 ^ 8192) & ~6144ull};
            const uint64_t q8[3] = {p8 ^ 1024, (p8 ^ 2048) & ~1024ull, (p8 ^ 4096) & ~3072ull};
            while (clk() - c0 < DELAY_EARLY) {}
            STAMPW(34);
            SFOR(H, 0, 2)
                int n = 0;
#pragma unroll 1
                for (; n < SPIN_LIMIT; n++) {
                    if (H == 0 || n > 0) { load_o<2 * H>(oa[2 * H], q16[2 * H], q8[2 * H]); load_o<2 * H + 1>(oa[2 * H + 1], q16[H + 1], q8[H + 1]); }
                    if (__all_sync(0xffffffffu, max(max_o<2 * H>(oa[2 * H]), max_o<1>(oa[2 * H + 1])) != SENT)) break;
                }
                STAMPW(22 + 2 * H);
                mbar_wait(bars + 8 * (B_FULL + 16 + H));
                if (H == 0) { bar_sync<2, 256>(); load_o<2>(oa[2], q16[2], q8[2]); load_o<3>(oa[3], q16[2], q8[2]); }
                wg_fence();
                SFOR(B, 2 * H, 2 * H + 2)
                    SFOR(i, (B ? 0 : 4), 8) Mma<144>::rs<1, tile_o(2 * B + i / 4) / 16 + (i & 3) * 128>(ao, oa[B][i], db); SEND
                    Mma<144>::rs<1, tile_o(2 * B) / 16 + 512>(ao, oa[B][8], dp);
                SEND
                wg_commit();
            SEND
            const int l2 = t2 & 31;
            const uint32_t mb = sb + q * 4096, tb = sb + 16384 + q * 512;
            const uint32_t ro = mb + (l2 & 15) * 128, sw = ((l2 >> 4) ^ (l2 & 7)) << 4;
            int row0 = r * 128 + hh * 64 + q * 16, cl = cb * 2, ct = 512 + cb * 16;
            asm volatile("" : "+r"(row0), "+r"(cl), "+r"(ct));
            wg_wait<1>();
            bar_sync<3, 128>();
            wg_wait<0>();
            pin(ao);
            STAMPW(30);
#pragma unroll
            for (int i = 0; i < 9; i++) {
                const float* a = ao + 8 * i;
                stsm4(i < 8 ? ro + (i >> 2) * 2048 + (sw ^ (32 * (i & 3))) : tb + (l2 & 15) * 32 + (l2 >> 4) * 16,
                      pack(a[0], a[1]), pack(a[2], a[3]), pack(a[4], a[5]), pack(a[6], a[7]));
            }
            fence_async();
            __syncwarp();
            if (elect()) {
                tma_st3(&mp.out, mb, 0, row0, cl);
                tma_st2(&mp.outt, tb, ct, row0);
                asm volatile("cp.async.bulk.commit_group;" ::: "memory");
                asm volatile("cp.async.bulk.wait_group.read 0;" ::: "memory");
            }
            STAMPW(32);
            GT(1);
        }
        if (t == 0) { DUMP(w, 40, 2); }
    }
}

typedef CUresult (*EncodeFn)(CUtensorMap*, CUtensorMapDataType, cuuint32_t, void*, const cuuint64_t*, const cuuint64_t*,
                             const cuuint32_t*, const cuuint32_t*, CUtensorMapInterleave, CUtensorMapSwizzle,
                             CUtensorMapL2promotion, CUtensorMapFloatOOBfill);

void encode(EncodeFn fn, CUtensorMap* m, const void* base, int rank, const cuuint64_t* dims, const cuuint64_t* strides,
            const cuuint32_t* box, CUtensorMapSwizzle sw) {
    const cuuint32_t es[4] = {1, 1, 1, 1};
    fn(m, CU_TENSOR_MAP_DATA_TYPE_BFLOAT16, rank, const_cast<void*>(base), dims, strides, box, es, CU_TENSOR_MAP_INTERLEAVE_NONE, sw,
       CU_TENSOR_MAP_L2_PROMOTION_L2_128B, CU_TENSOR_MAP_FLOAT_OOB_FILL_NONE);
}

}

extern "C" void kernel_launch(void* const* d_in, const int* in_sizes, int n_in, void* d_out, int out_size) {
    (void)in_sizes; (void)n_in; (void)out_size;
    static EncodeFn fn = nullptr;
    static Scratch* sc = nullptr;
    if (!fn) {
        void* p = nullptr;
        cudaDriverEntryPointQueryResult qr;
        cudaGetDriverEntryPoint("cuTensorMapEncodeTiled", &p, cudaEnableDefault, &qr);
        fn = (EncodeFn)p;
        cudaGetSymbolAddress((void**)&sc, g_scratch);
        cudaFuncSetAttribute(lab_kernel, cudaFuncAttributeMaxDynamicSharedMemorySize, SMEM_BYTES);
        cudaFuncAttributes fa; int dev = 0, res = 0;
        cudaFuncGetAttributes(&fa, lab_kernel);
        cudaGetDevice(&dev);
        cudaDeviceGetAttribute(&res, cudaDevAttrReservedSharedMemoryPerBlock, dev);
        if (fa.sharedSizeBytes != 0 || res != 1024 || ((uintptr_t)sc & 16383)) sc = nullptr;
    }
    if (!sc) return;
    const void *x = d_in[0], *wqkv = d_in[1], *wo = d_in[2];
    Zeros zs = {};
    for (int g = 0; g < 8; g++) for (int i = 0; i < 4; i++) {
        uint64_t* d = zs.d[g < 4 ? g : 7 - g][g >> 2][i];
        d[0] = desc(sb, 0, 1024, 1) + (g == 7 ? 7 << 16 : g >= 4 ? 0 : g);
        d[1] = desc(sb, 0, 1024, 1) + (g >= 4 ? g : 0);
        d[2] = desc(sb, 2048, 256, 3);
    }
    Maps mp;
    const auto SW = CU_TENSOR_MAP_SWIZZLE_128B;
    { cuuint64_t d[4] = {64, 2048, 1, 9}, s[3] = {1152, 128, 128}; cuuint32_t b[4] = {64, 128, 1, 1}; encode(fn, &mp.x, x, 4, d, s, b, SW); }
    { cuuint64_t d[4] = {1728, 64, 1, 9}, s[3] = {3456, 3456, 64 * 3456}; cuuint32_t b[4] = {64, 64, 1, 1}; encode(fn, &mp.w, wqkv, 4, d, s, b, SW); }
    { cuuint64_t d[4] = {576, 64, 3, 9}, s[3] = {3456, 1152, 64 * 3456}; cuuint32_t b[4] = {16, 64, 2, 1}; encode(fn, &mp.w16, wqkv, 4, d, s, b, CU_TENSOR_MAP_SWIZZLE_32B); }
    { cuuint64_t d[4] = {64, 72, 9, 8}, s[3] = {1152, 128, 72 * 1152}; cuuint32_t b[4] = {64, 72, 2, 1}; encode(fn, &mp.wo, wo, 4, d, s, b, SW); }
    { cuuint64_t d[4] = {576, 72, 1, 8}, s[3] = {1152, 1152, 72 * 1152}; cuuint32_t b[4] = {16, 72, 1, 1}; encode(fn, &mp.wot, wo, 4, d, s, b, SW); }
    { cuuint64_t d[3] = {64, 2048, 9}, s[2] = {1152, 128}; cuuint32_t b[3] = {64, 16, 2}; encode(fn, &mp.out, d_out, 3, d, s, b, SW); }
    { cuuint64_t d[2] = {576, 2048}, s[1] = {1152}; cuuint32_t b[2] = {16, 16}; encode(fn, &mp.outt, d_out, 2, d, s, b, CU_TENSOR_MAP_SWIZZLE_NONE); }
    lab_kernel<<<dim3(4, 4, 8), 384, SMEM_BYTES, cudaStreamPerThread>>>(sc, zs, mp);
}
```

```cpp
#include <cuda_runtime.h>
#include <cuda_bf16.h>
#include <cuda.h>
#include <stdint.h>
#include <stddef.h>
#include <type_traits>

namespace {
#define VSCH 0x044443333224ull

__host__ __device__ constexpr int slot_k(int c) { constexpr int t[4] = {150, 54, 102, 0}; return t[c & 3] * 1024; }
__host__ __device__ constexpr int slot_v(int c) { constexpr int t[9] = {134, 166, 182, 86, 134, 166, 182, 18, 198}; return t[c] * 1024; }
__host__ __device__ constexpr int slot_x(int c) { constexpr int t[5] = {18, 70, 118, 38, 198}; return t[c % 5] * 1024; }
__host__ __device__ constexpr int v_lo(int s) { int n = 0; for (int i = 0; i < s; i++) n += (int)(VSCH >> (44 - 4 * i)) & 15; return n; }
__host__ __device__ constexpr int v_step(int k) { int s = 0; while (v_lo(s + 1) <= k) s++; return s; }
constexpr int OFF_PK = 0, OFF_V = 18432;
__host__ __device__ constexpr int tile_q(int j) { return (54 + 18 * j) * 1024; }
__host__ __device__ constexpr int tile_o(int p) { return 27648 * p; }
constexpr int OFF_BKV = 218 * 1024;
static_assert(v_lo(12) == 36 && v_lo(11) >= 32 && v_step(4) >= 2 && v_step(8) >= 3, "v schedule");
constexpr int OFF_BAR = OFF_BKV + 7680;
constexpr int SMEM_BYTES = 232448;
constexpr int B_F0 = 0;
constexpr int B_FULL = 1;
constexpr int B_INIT = 45;
constexpr int B_EMP = 25;
#define Q_A 3
#define Q_B 4
#define Q_GO 34
#define XPROMO CU_TENSOR_MAP_L2_PROMOTION_L2_128B
#define SENT_0 400
#define SENT_P 140
#define PK_1 6
#define PK_2 12
#define QW0 0
#define O_K 5
#define O_F 1
#define V7AT 4
#define V8AT 5
#define OWN_LATE 1
#define PIECES 22
#define DV 0
#define PFLATE 0
#define MAP 2
#define PHI_K 0
#define PHI_Q 0
#define DELAY_EARLY 900
#define DELAY_LATE 900
constexpr uint32_t SENT = 0xFFFFFFFFu;
constexpr int SPIN_LIMIT = 1 << 17;

struct __align__(65536) Scratch {
    uint4 o[32 * 4 * 8 * 128];
    uint2 oh[32 * 8 * 128];
    float4 kv[8 * 2 * 4 * 96];
    unsigned init;
};
__device__ Scratch g_scratch;
#define GT(i) do {} while (0)
#define CLK(v) do {} while (0)
#define PUT(i, v) do {} while (0)
#define STAMP(i) do {} while (0)
#define STAMPW(i) do {} while (0)
#define DUMP(lo, hi, step) do {} while (0)

__device__ __forceinline__ void mbar_init(uint32_t bar, uint32_t cnt) { asm volatile("mbarrier.init.shared::cta.b64 [%0], %1;" :: "r"(bar), "r"(cnt) : "memory"); }
__device__ __forceinline__ void mbar_arrive(uint32_t bar) { asm volatile("mbarrier.arrive.shared::cta.b64 _, [%0];" :: "r"(bar) : "memory"); }
__device__ __forceinline__ void mbar_wait(uint32_t bar) {
    asm volatile("{ .reg .pred p;\n"
                 "W: mbarrier.try_wait.parity.shared::cta.b64 p, [%0], 0;\n"
                 "@!p bra.uni W; }" :: "r"(bar) : "memory");
}
__device__ __forceinline__ bool elect() {
    uint32_t p; asm volatile("{ .reg .pred q; elect.sync _|q, 0xffffffff; selp.u32 %0, 1, 0, q; }" : "=r"(p)); return p;
}
__device__ __forceinline__ void mbar_expect(uint32_t bar, uint32_t bytes) { asm volatile("mbarrier.arrive.expect_tx.shared::cta.b64 _, [%0], %1;" :: "r"(bar), "r"(bytes) : "memory"); }
__device__ __forceinline__ void tma4(uint32_t dst, const CUtensorMap* m, int c0, int c1, int c2, int c3, uint32_t bar) {
    asm volatile("cp.async.bulk.tensor.4d.shared::cluster.global.mbarrier::complete_tx::bytes [%0], [%1, {%3, %4, %5, %6}], [%2];"
                 :: "r"(dst), "l"(m), "r"(bar), "r"(c0), "r"(c1), "r"(c2), "r"(c3) : "memory");
}
__device__ __forceinline__ void tma_st2(const CUtensorMap* m, uint32_t src, int c0, int c1) {
    asm volatile("cp.async.bulk.tensor.2d.global.shared::cta.bulk_group [%0, {%2, %3}], [%1];" :: "l"(m), "r"(src), "r"(c0), "r"(c1) : "memory");
}
__device__ __forceinline__ void pf_map(const CUtensorMap* m) { asm volatile("prefetch.tensormap [%0];" :: "l"(m) : "memory"); }
__device__ __forceinline__ void fence_async() { asm volatile("fence.proxy.async.shared::cta;" ::: "memory"); }
template <int ID, int N> __device__ __forceinline__ void bar_sync() { asm volatile("bar.sync %0, %1;" :: "n"(ID), "n"(N) : "memory"); }
template <int ID, int N> __device__ __forceinline__ void bar_arrive() { asm volatile("bar.arrive %0, %1;" :: "n"(ID), "n"(N) : "memory"); }
__device__ __forceinline__ void wg_fence() { asm volatile("wgmma.fence.sync.aligned;" ::: "memory"); }
__device__ __forceinline__ void wg_commit() { asm volatile("wgmma.commit_group.sync.aligned;" ::: "memory"); }
template <int N> __device__ __forceinline__ void wg_wait() { asm volatile("wgmma.wait_group.sync.aligned %0;" :: "n"(N) : "memory"); }
template <int N> __device__ __forceinline__ void pin(float (&d)[N]) {
#pragma unroll
    for (int i = 0; i < N; i++) asm volatile("" : "+f"(d[i]) :: "memory");
}
__host__ __device__ constexpr uint64_t desc(uint32_t addr, uint32_t lbo, uint32_t sbo, uint64_t sw) {
    return (addr >> 4) | ((uint64_t)(lbo >> 4) << 16) | ((uint64_t)(sbo >> 4) << 32) | (sw << 62);
}
__device__ __forceinline__ void ldsm4(uint32_t (&r)[4], uint32_t a) {
    asm volatile("ldmatrix.sync.aligned.m8n8.x4.shared.b16 {%0,%1,%2,%3}, [%4];" : "=r"(r[0]), "=r"(r[1]), "=r"(r[2]), "=r"(r[3]) : "r"(a) : "memory");
}
__device__ __forceinline__ void stsm4(uint32_t a, uint32_t r0, uint32_t r1, uint32_t r2, uint32_t r3) {
    asm volatile("stmatrix.sync.aligned.m8n8.x4.shared.b16 [%0], {%1,%2,%3,%4};" :: "r"(a), "r"(r0), "r"(r1), "r"(r2), "r"(r3) : "memory");
}
__device__ __forceinline__ void stsm2(uint32_t a, uint32_t r0, uint32_t r1) {
    asm volatile("stmatrix.sync.aligned.m8n8.x2.shared.b16 [%0], {%1,%2};" :: "r"(a), "r"(r0), "r"(r1) : "memory");
}
__device__ __forceinline__ void lds128(uint32_t (&r)[4], uint32_t a) {
    asm volatile("ld.shared.v4.b32 {%0,%1,%2,%3}, [%4];" : "=r"(r[0]), "=r"(r[1]), "=r"(r[2]), "=r"(r[3]) : "r"(a) : "memory");
}
__device__ __forceinline__ void sts128(uint32_t a, const uint32_t (&r)[4]) {
    asm volatile("st.shared.v4.b32 [%4], {%0,%1,%2,%3};" :: "r"(r[0]), "r"(r[1]), "r"(r[2]), "r"(r[3]), "r"(a) : "memory");
}
__device__ __forceinline__ void sts32(uint32_t a, uint32_t v) { asm volatile("st.shared.b32 [%0], %1;" :: "r"(a), "r"(v) : "memory"); }
__device__ __forceinline__ uint32_t pack(float lo, float hi) {
    uint32_t r; asm("cvt.rn.bf16x2.f32 %0, %1, %2;" : "=r"(r) : "f"(hi), "f"(lo)); return r;
}
__device__ __forceinline__ uint32_t pack_v(float lo, float hi) {
    uint32_t r; asm volatile("cvt.rn.bf16x2.f32 %0, %1, %2;" : "=r"(r) : "f"(hi), "f"(lo)); return r;
}
template <int F32>
__device__ __forceinline__ uint32_t phi2(float lo, float hi) {
    uint32_t r;
    if (F32) asm volatile("{ .reg .f32 a, b, u, v;\n"
        "mul.f32 a, %1, 0f3FB8AA3B; mul.f32 b, %2, 0f3FB8AA3B; ex2.approx.ftz.f32 a, a; ex2.approx.ftz.f32 b, b;\n"
        "add.sat.f32 a, a, 0f358637BD; add.sat.f32 b, b, 0f358637BD;\n"
        "abs.f32 u, %1; add.f32 u, u, %1; abs.f32 v, %2; add.f32 v, v, %2;\n"
        "fma.rn.f32 a, u, 0f3F000000, a; fma.rn.f32 b, v, 0f3F000000, b; cvt.rn.bf16x2.f32 %0, b, a; }" : "=r"(r) : "f"(lo), "f"(hi));
    else asm volatile("{ .reg .f32 a, b; .reg .b32 e, t;\n"
        "mul.f32 a, %1, 0f3FB8AA3B; mul.f32 b, %2, 0f3FB8AA3B; ex2.approx.ftz.f32 a, a; ex2.approx.ftz.f32 b, b;\n"
        "add.sat.f32 a, a, 0f358637BD; add.sat.f32 b, b, 0f358637BD;\n"
        "cvt.rn.bf16x2.f32 e, b, a; cvt.rn.relu.bf16x2.f32 t, %2, %1; add.rn.bf16x2 %0, e, t; }" : "=r"(r) : "f"(lo), "f"(hi));
    return r;
}
__device__ __forceinline__ float rcp(float t) { float r; asm("rcp.approx.ftz.f32 %0, %1;" : "=f"(r) : "f"(t)); return r; }
template <int OFF> __device__ __forceinline__ void st128(void* p, uint32_t a, uint32_t b, uint32_t c, uint32_t d) {
    asm volatile("{ .reg .b128 v; .reg .b64 lo, hi; mov.b64 lo, {%1,%2}; mov.b64 hi, {%3,%4}; mov.b128 v, {lo,hi};\n"
                 "st.relaxed.gpu.global.b128 [%0 + %5], v; }" :: "l"(p), "r"(a), "r"(b), "r"(c), "r"(d), "n"(OFF) : "memory");
}
template <int OFF> __device__ __forceinline__ void st64(void* p, uint32_t a, uint32_t b) {
    asm volatile("{ .reg .b64 v; mov.b64 v, {%1,%2}; st.relaxed.gpu.global.b64 [%0 + %3], v; }" :: "l"(p), "r"(a), "r"(b), "n"(OFF) : "memory");
}
template <int OFF> __device__ __forceinline__ void ld128(uint32_t (&r)[4], const void* p) {
    asm volatile("{ .reg .b128 v; .reg .b64 lo, hi; ld.relaxed.gpu.global.b128 v, [%4 + %5]; mov.b128 {lo,hi}, v;\n"
                 "mov.b64 {%0,%1}, lo; mov.b64 {%2,%3}, hi; }" : "=r"(r[0]), "=r"(r[1]), "=r"(r[2]), "=r"(r[3]) : "l"(p), "n"(OFF) : "memory");
}
template <int OFF> __device__ __forceinline__ void ld64(uint32_t& a, uint32_t& b, const void* p) {
    asm volatile("{ .reg .b64 v; ld.relaxed.gpu.global.b64 v, [%2 + %3]; mov.b64 {%0,%1}, v; }" : "=r"(a), "=r"(b) : "l"(p), "n"(OFF) : "memory");
}
__device__ __forceinline__ unsigned ld_acq(const unsigned* p) { unsigned v; asm volatile("ld.acquire.gpu.global.u32 %0, [%1];" : "=r"(v) : "l"(p) : "memory"); return v; }
__device__ __forceinline__ unsigned inc_rel(unsigned* p) { unsigned v; asm volatile("atom.release.gpu.global.add.u32 %0, [%1], 1;" : "=r"(v) : "l"(p) : "memory"); return v; }
template <int OFF> __device__ __forceinline__ void red4(void* p, float a, float b, float c, float d) {
    asm volatile("red.relaxed.gpu.global.add.v4.f32 [%0 + %5], {%1,%2,%3,%4};" :: "l"(p), "f"(a), "f"(b), "f"(c), "f"(d), "n"(OFF) : "memory");
}
__device__ __forceinline__ unsigned clk() { unsigned v; asm volatile("mov.u32 %0, %%clock;" : "=r"(v) :: "memory"); return v; }
__device__ __forceinline__ int fresh_tid() { int v; asm volatile("mov.u32 %0, %%tid.x;" : "=r"(v)); return v; }
template <int N> struct Mma;
template <> struct Mma<16> {
    template <int ACC, int OB> static __device__ __forceinline__ void rs(float* d, const uint32_t (&a)[4], uint64_t b) {
        asm volatile("{ .reg .pred p; .reg .b64 db; add.s64 db, %12, %14; setp.ne.b32 p, %13, 0;\n"
            "wgmma.mma_async.sync.aligned.m64n16k16.f32.bf16.bf16 {%0,%1,%2,%3,%4,%5,%6,%7},\n"
            "{%8,%9,%10,%11}, db, p, 1, 1, 1; }"
            : "+f"(d[0]), "+f"(d[1]), "+f"(d[2]), "+f"(d[3]), "+f"(d[4]), "+f"(d[5]), "+f"(d[6]), "+f"(d[7])
            : "r"(a[0]), "r"(a[1]), "r"(a[2]), "r"(a[3]), "l"(b), "n"(ACC), "n"(OB));
    }
    template <int ACC, int OA, int OB, int TA> static __device__ __forceinline__ void ss(float* d, uint64_t a, uint64_t b) {
        asm volatile("{ .reg .pred p; .reg .b64 da, db; add.s64 da, %8, %11; add.s64 db, %9, %12; setp.ne.b32 p, %10, 0;\n"
            "wgmma.mma_async.sync.aligned.m64n16k16.f32.bf16.bf16 {%0,%1,%2,%3,%4,%5,%6,%7},\n"
            "da, db, p, 1, 1, %13, 1; }"
            : "+f"(d[0]), "+f"(d[1]), "+f"(d[2]), "+f"(d[3]), "+f"(d[4]), "+f"(d[5]), "+f"(d[6]), "+f"(d[7])
            : "l"(a), "l"(b), "n"(ACC), "n"(OA), "n"(OB), "n"(TA));
    }
};
template <> struct Mma<24> {
    template <int ACC, int OB> static __device__ __forceinline__ void rs(float* d, const uint32_t (&a)[4], uint64_t b) {
        asm volatile("{ .reg .pred p; .reg .b64 db; add.s64 db, %16, %18; setp.ne.b32 p, %17, 0;\n"
            "wgmma.mma_async.sync.aligned.m64n24k16.f32.bf16.bf16 {%0,%1,%2,%3,%4,%5,%6,%7,%8,%9,%10,%11},\n"
            "{%12,%13,%14,%15}, db, p, 1, 1, 1; }"
            : "+f"(d[0]), "+f"(d[1]), "+f"(d[2]), "+f"(d[3]), "+f"(d[4]), "+f"(d[5]), "+f"(d[6]), "+f"(d[7]), "+f"(d[8]), "+f"(d[9]), "+f"(d[10]), "+f"(d[11])
            : "r"(a[0]), "r"(a[1]), "r"(a[2]), "r"(a[3]), "l"(b), "n"(ACC), "n"(OB));
    }
    template <int ACC, int OA, int OB, int TA> static __device__ __forceinline__ void ss(float* d, uint64_t a, uint64_t b) {
        asm volatile("{ .reg .pred p; .reg .b64 da, db; add.s64 da, %12, %15; add.s64 db, %13, %16; setp.ne.b32 p, %14, 0;\n"
            "wgmma.mma_async.sync.aligned.m64n24k16.f32.bf16.bf16 {%0,%1,%2,%3,%4,%5,%6,%7,%8,%9,%10,%11},\n"
            "da, db, p, 1, 1, %17, 1; }"
            : "+f"(d[0]), "+f"(d[1]), "+f"(d[2]), "+f"(d[3]), "+f"(d[4]), "+f"(d[5]), "+f"(d[6]), "+f"(d[7]), "+f"(d[8]), "+f"(d[9]), "+f"(d[10]), "+f"(d[11])
            : "l"(a), "l"(b), "n"(ACC), "n"(OA), "n"(OB), "n"(TA));
    }
};
template <> struct Mma<32> {
    template <int ACC, int OB> static __device__ __forceinline__ void rs(float* d, const uint32_t (&a)[4], uint64_t b) {
        asm volatile("{ .reg .pred p; .reg .b64 db; add.s64 db, %20, %22; setp.ne.b32 p, %21, 0;\n"
            "wgmma.mma_async.sync.aligned.m64n32k16.f32.bf16.bf16 {%0,%1,%2,%3,%4,%5,%6,%7,%8,%9,%10,%11,%12,%13,%14,%15},\n"
            "{%16,%17,%18,%19}, db, p, 1, 1, 1; }"
            : "+f"(d[0]), "+f"(d[1]), "+f"(d[2]), "+f"(d[3]), "+f"(d[4]), "+f"(d[5]), "+f"(d[6]), "+f"(d[7]), "+f"(d[8]), "+f"(d[9]), "+f"(d[10]), "+f"(d[11]), "+f"(d[12]), "+f"(d[13]), "+f"(d[14]), "+f"(d[15])
            : "r"(a[0]), "r"(a[1]), "r"(a[2]), "r"(a[3]), "l"(b), "n"(ACC), "n"(OB));
    }
    template <int ACC, int OA, int OB, int TA> static __device__ __forceinline__ void ss(float* d, uint64_t a, uint64_t b) {
        asm volatile("{ .reg .pred p; .reg .b64 da, db; add.s64 da, %16, %19; add.s64 db, %17, %20; setp.ne.b32 p, %18, 0;\n"
            "wgmma.mma_async.sync.aligned.m64n32k16.f32.bf16.bf16 {%0,%1,%2,%3,%4,%5,%6,%7,%8,%9,%10,%11,%12,%13,%14,%15},\n"
            "da, db, p, 1, 1, %21, 1; }"
            : "+f"(d[0]), "+f"(d[1]), "+f"(d[2]), "+f"(d[3]), "+f"(d[4]), "+f"(d[5]), "+f"(d[6]), "+f"(d[7]), "+f"(d[8]), "+f"(d[9]), "+f"(d[10]), "+f"(d[11]), "+f"(d[12]), "+f"(d[13]), "+f"(d[14]), "+f"(d[15])
            : "l"(a), "l"(b), "n"(ACC), "n"(OA), "n"(OB), "n"(TA));
    }
};
template <> struct Mma<40> {
    template <int ACC, int OB> static __device__ __forceinline__ void rs(float* d, const uint32_t (&a)[4], uint64_t b) {
        asm volatile("{ .reg .pred p; .reg .b64 db; add.s64 db, %24, %26; setp.ne.b32 p, %25, 0;\n"
            "wgmma.mma_async.sync.aligned.m64n40k16.f32.bf16.bf16 {%0,%1,%2,%3,%4,%5,%6,%7,%8,%9,%10,%11,%12,%13,%14,%15,%16,%17,%18,%19},\n"
            "{%20,%21,%22,%23}, db, p, 1, 1, 1; }"
            : "+f"(d[0]), "+f"(d[1]), "+f"(d[2]), "+f"(d[3]), "+f"(d[4]), "+f"(d[5]), "+f"(d[6]), "+f"(d[7]), "+f"(d[8]), "+f"(d[9]), "+f"(d[10]), "+f"(d[11]), "+f"(d[12]), "+f"(d[13]), "+f"(d[14]), "+f"(d[15]), "+f"(d[16]), "+f"(d[17]), "+f"(d[18]), "+f"(d[19])
            : "r"(a[0]), "r"(a[1]), "r"(a[2]), "r"(a[3]), "l"(b), "n"(ACC), "n"(OB));
    }
    template <int ACC, int OA, int OB, int TA> static __device__ __forceinline__ void ss(float* d, uint64_t a, uint64_t b) {
        asm volatile("{ .reg .pred p; .reg .b64 da, db; add.s64 da, %20, %23; add.s64 db, %21, %24; setp.ne.b32 p, %22, 0;\n"
            "wgmma.mma_async.sync.aligned.m64n40k16.f32.bf16.bf16 {%0,%1,%2,%3,%4,%5,%6,%7,%8,%9,%10,%11,%12,%13,%14,%15,%16,%17,%18,%19},\n"
            "da, db, p, 1, 1, %25, 1; }"
            : "+f"(d[0]), "+f"(d[1]), "+f"(d[2]), "+f"(d[3]), "+f"(d[4]), "+f"(d[5]), "+f"(d[6]), "+f"(d[7]), "+f"(d[8]), "+f"(d[9]), "+f"(d[10]), "+f"(d[11]), "+f"(d[12]), "+f"(d[13]), "+f"(d[14]), "+f"(d[15]), "+f"(d[16]), "+f"(d[17]), "+f"(d[18]), "+f"(d[19])
            : "l"(a), "l"(b), "n"(ACC), "n"(OA), "n"(OB), "n"(TA));
    }
};
template <> struct Mma<48> {
    template <int ACC, int OB> static __device__ __forceinline__ void rs(float* d, const uint32_t (&a)[4], uint64_t b) {
        asm volatile("{ .reg .pred p; .reg .b64 db; add.s64 db, %28, %30; setp.ne.b32 p, %29, 0;\n"
            "wgmma.mma_async.sync.aligned.m64n48k16.f32.bf16.bf16 {%0,%1,%2,%3,%4,%5,%6,%7,%8,%9,%10,%11,%12,%13,%14,%15,%16,%17,%18,%19,%20,%21,%22,%23},\n"
            "{%24,%25,%26,%27}, db, p, 1, 1, 1; }"
            : "+f"(d[0]), "+f"(d[1]), "+f"(d[2]), "+f"(d[3]), "+f"(d[4]), "+f"(d[5]), "+f"(d[6]), "+f"(d[7]), "+f"(d[8]), "+f"(d[9]), "+f"(d[10]), "+f"(d[11]), "+f"(d[12]), "+f"(d[13]), "+f"(d[14]), "+f"(d[15]), "+f"(d[16]), "+f"(d[17]), "+f"(d[18]), "+f"(d[19]), "+f"(d[20]), "+f"(d[21]), "+f"(d[22]), "+f"(d[23])
            : "r"(a[0]), "r"(a[1]), "r"(a[2]), "r"(a[3]), "l"(b), "n"(ACC), "n"(OB));
    }
    template <int ACC, int OA, int OB, int TA> static __device__ __forceinline__ void ss(float* d, uint64_t a, uint64_t b) {
        asm volatile("{ .reg .pred p; .reg .b64 da, db; add.s64 da, %24, %27; add.s64 db, %25, %28; setp.ne.b32 p, %26, 0;\n"
            "wgmma.mma_async.sync.aligned.m64n48k16.f32.bf16.bf16 {%0,%1,%2,%3,%4,%5,%6,%7,%8,%9,%10,%11,%12,%13,%14,%15,%16,%17,%18,%19,%20,%21,%22,%23},\n"
            "da, db, p, 1, 1, %29, 1; }"
            : "+f"(d[0]), "+f"(d[1]), "+f"(d[2]), "+f"(d[3]), "+f"(d[4]), "+f"(d[5]), "+f"(d[6]), "+f"(d[7]), "+f"(d[8]), "+f"(d[9]), "+f"(d[10]), "+f"(d[11]), "+f"(d[12]), "+f"(d[13]), "+f"(d[14]), "+f"(d[15]), "+f"(d[16]), "+f"(d[17]), "+f"(d[18]), "+f"(d[19]), "+f"(d[20]), "+f"(d[21]), "+f"(d[22]), "+f"(d[23])
            : "l"(a), "l"(b), "n"(ACC), "n"(OA), "n"(OB), "n"(TA));
    }
};
template <> struct Mma<56> {
    template <int ACC, int OB> static __device__ __forceinline__ void rs(float* d, const uint32_t (&a)[4], uint64_t b) {
        asm volatile("{ .reg .pred p; .reg .b64 db; add.s64 db, %32, %34; setp.ne.b32 p, %33, 0;\n"
            "wgmma.mma_async.sync.aligned.m64n56k16.f32.bf16.bf16 {%0,%1,%2,%3,%4,%5,%6,%7,%8,%9,%10,%11,%12,%13,%14,%15,%16,%17,%18,%19,%20,%21,%22,%23,%24,%25,%26,%27},\n"
            "{%28,%29,%30,%31}, db, p, 1, 1, 1; }"
            : "+f"(d[0]), "+f"(d[1]), "+f"(d[2]), "+f"(d[3]), "+f"(d[4]), "+f"(d[5]), "+f"(d[6]), "+f"(d[7]), "+f"(d[8]), "+f"(d[9]), "+f"(d[10]), "+f"(d[11]), "+f"(d[12]), "+f"(d[13]), "+f"(d[14]), "+f"(d[15]), "+f"(d[16]), "+f"(d[17]), "+f"(d[18]), "+f"(d[19]), "+f"(d[20]), "+f"(d[21]), "+f"(d[22]), "+f"(d[23]), "+f"(d[24]), "+f"(d[25]), "+f"(d[26]), "+f"(d[27])
            : "r"(a[0]), "r"(a[1]), "r"(a[2]), "r"(a[3]), "l"(b), "n"(ACC), "n"(OB));
    }
    template <int ACC, int OA, int OB, int TA> static __device__ __forceinline__ void ss(float* d, uint64_t a, uint64_t b) {
        asm volatile("{ .reg .pred p; .reg .b64 da, db; add.s64 da, %28, %31; add.s64 db, %29, %32; setp.ne.b32 p, %30, 0;\n"
            "wgmma.mma_async.sync.aligned.m64n56k16.f32.bf16.bf16 {%0,%1,%2,%3,%4,%5,%6,%7,%8,%9,%10,%11,%12,%13,%14,%15,%16,%17,%18,%19,%20,%21,%22,%23,%24,%25,%26,%27},\n"
            "da, db, p, 1, 1, %33, 1; }"
            : "+f"(d[0]), "+f"(d[1]), "+f"(d[2]), "+f"(d[3]), "+f"(d[4]), "+f"(d[5]), "+f"(d[6]), "+f"(d[7]), "+f"(d[8]), "+f"(d[9]), "+f"(d[10]), "+f"(d[11]), "+f"(d[12]), "+f"(d[13]), "+f"(d[14]), "+f"(d[15]), "+f"(d[16]), "+f"(d[17]), "+f"(d[18]), "+f"(d[19]), "+f"(d[20]), "+f"(d[21]), "+f"(d[22]), "+f"(d[23]), "+f"(d[24]), "+f"(d[25]), "+f"(d[26]), "+f"(d[27])
            : "l"(a), "l"(b), "n"(ACC), "n"(OA), "n"(OB), "n"(TA));
    }
};
template <> struct Mma<64> {
    template <int ACC, int OB> static __device__ __forceinline__ void rs(float* d, const uint32_t (&a)[4], uint64_t b) {
        asm volatile("{ .reg .pred p; .reg .b64 db; add.s64 db, %36, %38; setp.ne.b32 p, %37, 0;\n"
            "wgmma.mma_async.sync.aligned.m64n64k16.f32.bf16.bf16 {%0,%1,%2,%3,%4,%5,%6,%7,%8,%9,%10,%11,%12,%13,%14,%15,%16,%17,%18,%19,%20,%21,%22,%23,%24,%25,%26,%27,%28,%29,%30,%31},\n"
            "{%32,%33,%34,%35}, db, p, 1, 1, 1; }"
            : "+f"(d[0]), "+f"(d[1]), "+f"(d[2]), "+f"(d[3]), "+f"(d[4]), "+f"(d[5]), "+f"(d[6]), "+f"(d[7]), "+f"(d[8]), "+f"(d[9]), "+f"(d[10]), "+f"(d[11]), "+f"(d[12]), "+f"(d[13]), "+f"(d[14]), "+f"(d[15]), "+f"(d[16]), "+f"(d[17]), "+f"(d[18]), "+f"(d[19]), "+f"(d[20]), "+f"(d[21]), "+f"(d[22]), "+f"(d[23]), "+f"(d[24]), "+f"(d[25]), "+f"(d[26]), "+f"(d[27]), "+f"(d[28]), "+f"(d[29]), "+f"(d[30]), "+f"(d[31])
            : "r"(a[0]), "r"(a[1]), "r"(a[2]), "r"(a[3]), "l"(b), "n"(ACC), "n"(OB));
    }
};
template <> struct Mma<72> {
    template <int ACC, int OB> static __device__ __forceinline__ void rs(float* d, const uint32_t (&a)[4], uint64_t b) {
        asm volatile("{ .reg .pred p; .reg .b64 db; add.s64 db, %40, %42; setp.ne.b32 p, %41, 0;\n"
            "wgmma.mma_async.sync.aligned.m64n72k16.f32.bf16.bf16 {%0,%1,%2,%3,%4,%5,%6,%7,%8,%9,%10,%11,%12,%13,%14,%15,%16,%17,%18,%19,%20,%21,%22,%23,%24,%25,%26,%27,%28,%29,%30,%31,%32,%33,%34,%35},\n"
            "{%36,%37,%38,%39}, db, p, 1, 1, 1; }"
            : "+f"(d[0]), "+f"(d[1]), "+f"(d[2]), "+f"(d[3]), "+f"(d[4]), "+f"(d[5]), "+f"(d[6]), "+f"(d[7]), "+f"(d[8]), "+f"(d[9]), "+f"(d[10]), "+f"(d[11]), "+f"(d[12]), "+f"(d[13]), "+f"(d[14]), "+f"(d[15]), "+f"(d[16]), "+f"(d[17]), "+f"(d[18]), "+f"(d[19]), "+f"(d[20]), "+f"(d[21]), "+f"(d[22]), "+f"(d[23]), "+f"(d[24]), "+f"(d[25]), "+f"(d[26]), "+f"(d[27]), "+f"(d[28]), "+f"(d[29]), "+f"(d[30]), "+f"(d[31]), "+f"(d[32]), "+f"(d[33]), "+f"(d[34]), "+f"(d[35])
            : "r"(a[0]), "r"(a[1]), "r"(a[2]), "r"(a[3]), "l"(b), "n"(ACC), "n"(OB));
    }
    template <int ACC, int OA, int OB, int TA> static __device__ __forceinline__ void ss(float* d, uint64_t a, uint64_t b) {
        asm volatile("{ .reg .pred p; .reg .b64 da, db; add.s64 da, %36, %39; add.s64 db, %37, %40; setp.ne.b32 p, %38, 0;\n"
            "wgmma.mma_async.sync.aligned.m64n72k16.f32.bf16.bf16 {%0,%1,%2,%3,%4,%5,%6,%7,%8,%9,%10,%11,%12,%13,%14,%15,%16,%17,%18,%19,%20,%21,%22,%23,%24,%25,%26,%27,%28,%29,%30,%31,%32,%33,%34,%35},\n"
            "da, db, p, 1, 1, %41, 1; }"
            : "+f"(d[0]), "+f"(d[1]), "+f"(d[2]), "+f"(d[3]), "+f"(d[4]), "+f"(d[5]), "+f"(d[6]), "+f"(d[7]), "+f"(d[8]), "+f"(d[9]), "+f"(d[10]), "+f"(d[11]), "+f"(d[12]), "+f"(d[13]), "+f"(d[14]), "+f"(d[15]), "+f"(d[16]), "+f"(d[17]), "+f"(d[18]), "+f"(d[19]), "+f"(d[20]), "+f"(d[21]), "+f"(d[22]), "+f"(d[23]), "+f"(d[24]), "+f"(d[25]), "+f"(d[26]), "+f"(d[27]), "+f"(d[28]), "+f"(d[29]), "+f"(d[30]), "+f"(d[31]), "+f"(d[32]), "+f"(d[33]), "+f"(d[34]), "+f"(d[35])
            : "l"(a), "l"(b), "n"(ACC), "n"(OA), "n"(OB), "n"(TA));
    }
};
template <> struct Mma<80> {
    template <int ACC, int OB> static __device__ __forceinline__ void rs(float* d, const uint32_t (&a)[4], uint64_t b) {
        asm volatile("{ .reg .pred p; .reg .b64 db; add.s64 db, %44, %46; setp.ne.b32 p, %45, 0;\n"
            "wgmma.mma_async.sync.aligned.m64n80k16.f32.bf16.bf16 {%0,%1,%2,%3,%4,%5,%6,%7,%8,%9,%10,%11,%12,%13,%14,%15,%16,%17,%18,%19,%20,%21,%22,%23,%24,%25,%26,%27,%28,%29,%30,%31,%32,%33,%34,%35,%36,%37,%38,%39},\n"
            "{%40,%41,%42,%43}, db, p, 1, 1, 1; }"
            : "+f"(d[0]), "+f"(d[1]), "+f"(d[2]), "+f"(d[3]), "+f"(d[4]), "+f"(d[5]), "+f"(d[6]), "+f"(d[7]), "+f"(d[8]), "+f"(d[9]), "+f"(d[10]), "+f"(d[11]), "+f"(d[12]), "+f"(d[13]), "+f"(d[14]), "+f"(d[15]), "+f"(d[16]), "+f"(d[17]), "+f"(d[18]), "+f"(d[19]), "+f"(d[20]), "+f"(d[21]), "+f"(d[22]), "+f"(d[23]), "+f"(d[24]), "+f"(d[25]), "+f"(d[26]), "+f"(d[27]), "+f"(d[28]), "+f"(d[29]), "+f"(d[30]), "+f"(d[31]), "+f"(d[32]), "+f"(d[33]), "+f"(d[34]), "+f"(d[35]), "+f"(d[36]), "+f"(d[37]), "+f"(d[38]), "+f"(d[39])
            : "r"(a[0]), "r"(a[1]), "r"(a[2]), "r"(a[3]), "l"(b), "n"(ACC), "n"(OB));
    }
};
template <> struct Mma<144> {
    template <int ACC, int OB> static __device__ __forceinline__ void rs(float* d, const uint32_t (&a)[4], uint64_t b) {
        asm volatile("{ .reg .pred p; .reg .b64 db; add.s64 db, %76, %78; setp.ne.b32 p, %77, 0;\n"
            "wgmma.mma_async.sync.aligned.m64n144k16.f32.bf16.bf16 {%0,%1,%2,%3,%4,%5,%6,%7,%8,%9,%10,%11,%12,%13,%14,%15,%16,%17,%18,%19,%20,%21,%22,%23,%24,%25,%26,%27,%28,%29,%30,%31,%32,%33,%34,%35,%36,%37,%38,%39,%40,%41,%42,%43,%44,%45,%46,%47,%48,%49,%50,%51,%52,%53,%54,%55,%56,%57,%58,%59,%60,%61,%62,%63,%64,%65,%66,%67,%68,%69,%70,%71},\n"
            "{%72,%73,%74,%75}, db, p, 1, 1, 1; }"
            : "+f"(d[0]), "+f"(d[1]), "+f"(d[2]), "+f"(d[3]), "+f"(d[4]), "+f"(d[5]), "+f"(d[6]), "+f"(d[7]), "+f"(d[8]), "+f"(d[9]), "+f"(d[10]), "+f"(d[11]), "+f"(d[12]), "+f"(d[13]), "+f"(d[14]), "+f"(d[15]), "+f"(d[16]), "+f"(d[17]), "+f"(d[18]), "+f"(d[19]), "+f"(d[20]), "+f"(d[21]), "+f"(d[22]), "+f"(d[23]), "+f"(d[24]), "+f"(d[25]), "+f"(d[26]), "+f"(d[27]), "+f"(d[28]), "+f"(d[29]), "+f"(d[30]), "+f"(d[31]), "+f"(d[32]), "+f"(d[33]), "+f"(d[34]), "+f"(d[35]), "+f"(d[36]), "+f"(d[37]), "+f"(d[38]), "+f"(d[39]), "+f"(d[40]), "+f"(d[41]), "+f"(d[42]), "+f"(d[43]), "+f"(d[44]), "+f"(d[45]), "+f"(d[46]), "+f"(d[47]), "+f"(d[48]), "+f"(d[49]), "+f"(d[50]), "+f"(d[51]), "+f"(d[52]), "+f"(d[53]), "+f"(d[54]), "+f"(d[55]), "+f"(d[56]), "+f"(d[57]), "+f"(d[58]), "+f"(d[59]), "+f"(d[60]), "+f"(d[61]), "+f"(d[62]), "+f"(d[63]), "+f"(d[64]), "+f"(d[65]), "+f"(d[66]), "+f"(d[67]), "+f"(d[68]), "+f"(d[69]), "+f"(d[70]), "+f"(d[71])
            : "r"(a[0]), "r"(a[1]), "r"(a[2]), "r"(a[3]), "l"(b), "n"(ACC), "n"(OB));
    }
};

template <int I, int N, class F> __device__ __forceinline__ void static_for(F&& f) {
    if constexpr (I < N) { f(std::integral_constant<int, I>{}); static_for<I + 1, N>(f); }
}
#define SFOR(var, lo, hi) static_for<lo, hi>([&](auto var##_c) { constexpr int var = decltype(var##_c)::value;
#define SEND });
template <int N> constexpr std::integral_constant<int, N> IC{};

struct __align__(64) Tabs {
    uint64_t d[4][2][4][2];
    uint64_t n[4], z;
    uint32_t item[42];
    uint16_t strm[8][5][6];
    uint16_t bytes[2][20];
};
struct Maps { CUtensorMap x, w, w16, wo, wot, out, outt; };
constexpr uint32_t sb = 1024, bars = sb + OFF_BAR;

constexpr Tabs make_tabs() {
    Tabs zs = {};
    for (int g = 0; g < 8; g++) {
        const int hh = g >> 2, cb = g & 3, lm = (g + hh) * 64, lo = (g + 1 - hh) * 64, nar = g == 1 || g == 6;
        const int crs = nar || g == 2 || g == 5, lq = crs ? g * 64 + (g == 5 ? 32 : 48) : lo;
        for (int i = 0; i < 4; i++) {
            uint64_t* d = zs.d[hh ? 7 - g : g][hh][i];
            const bool cross = crs && i == 3;
            d[0] = desc(sb, 0, 1024, 1) + (g == 7 ? 7 << 16 : hh ? 2 * cross : g);
            d[1] = desc(sb, 0, 1024, 1) + (cross ? g == 5 : hh ? g : 0);
            zs.n[i] = desc(sb, 2048, 256, 3);
        }
        const int st[5][6] = {{576 + lm, nar ? 128 + hh * 304 : 576 + lo, 0, nar, 1 | (1 + nar) << 4 | 8 << 8, 3 | 8 << 8},
                              {1152 + lm, 1152 + lo, 0, 0, 1 | 1 << 4 | (nar ? 0 : 8) << 8, 11 | 17 << 8},
                              {0, 0, 0, 0, 0, 21 | 25 << 8},
                              {lm, lq, 0, 0, 1 | 1 << 4 | 8 << 8, 25 | 34 << 8},
                              {0, 512 + cb * 16, cb * 2, 0, 3 | 4 << 4 | 18 << 8, 34 | 42 << 8}};
        for (int i = 0; i < 30; i++) zs.strm[g][i / 6][i % 6] = st[i / 6][i % 6];
    }
    auto item = [](int dst, int full, int wait, int k, int gm) constexpr { return dst / 1024 | (B_FULL + full) << 8 | (wait + 1) << 13 | k << 20 | gm << 24; };
    for (int c = 0; c < 9; c++) {
        auto done = [](int cv) constexpr { const int s = v_step(4 * cv + 3); return s == 9 ? 10 : s; };
        auto mx = [](int a, int b) constexpr { return a > b ? a : b; };
        const int vfree[9] = {-1, -1, -1, B_F0, B_EMP + done(0), B_EMP + done(1), B_EMP + done(2), B_EMP + V7AT, B_EMP + V8AT};
        const int qfree[9] = {5, mx(5, done(3)), mx(6, done(3)), 6, mx(6, done(4)), mx(8, done(4)), mx(8, done(5)), mx(done(5), done(6)), 11};
        if (c) zs.item[c - 1] = item(slot_k(c), c, c < 4 ? -1 : B_EMP + c - 4, c, 0);
        zs.item[8 + c] = item(slot_v(c), c < 3 ? c + 1 : v_step(4 * c), vfree[c], c, 0);
        if (c) zs.item[16 + c] = item(slot_x(c), c - 1, c < 5 ? -1 : B_EMP + (c < 6 ? 0 : c - 6), c, 0);
        zs.item[25 + c] = item(tile_q(c), 12 + c / 3, B_EMP + qfree[c], c, 0);
        if (c < 8) zs.item[34 + c] = item(tile_o(c), 15 + (c < 4 ? c / 2 : 2), B_EMP + (c < 1 ? 12 : c + 11), c, c < 2 ? 7 : c < 4 ? 6 : 4);
    }
    for (int nar = 0; nar < 2; nar++) {
        zs.bytes[nar][B_F0] = 128 - 16 * nar;
        for (int i = 0; i < 42; i++) zs.bytes[nar][zs.item[i] >> 8 & 31] += i < 8 ? 64 - 16 * nar : i < 17 ? 64 - 32 * nar : i < 34 ? 64 : 81;
    }
    return zs;
}

__device__ __forceinline__ void load_kv(uint32_t (&s)[8][4], const void* p) { SFOR(u, 0, 8) ld128<u * 1536>(s[u], p); SEND }

template <int V>
__device__ __forceinline__ void front(uint32_t (&pq)[5][4], uint32_t (&ks)[8][4], Scratch* sc, int g, int hh, int w, int q, bool lead, const Tabs& zs) {
    const uint64_t dz = zs.z;
    constexpr int NQ = V == 1 ? 40 : V == 2 ? 32 : 64 - 8 * V, NB = 64 - 8 * V, NS = 72 - NB;
    const int lane = threadIdx.x & 31, c = lane & 3, half = hh ^ w;
    const uint32_t xo = sb + (half * 64 + q * 16 + (lane & 15)) * 128, xs = ((lane >> 4) ^ (lane & 7)) << 4;
    const uint64_t dx = dz + desc(sb, 16, 1024, 1) + half * 512;
    uint64_t dm, dt, dn;
    auto rebase = [&](int i) { dm = zs.d[V][hh][i][0]; dt = zs.d[V][hh][i][1]; dn = zs.n[i]; };
    uint32_t xa[36][4];
    auto mma = [&](auto N, auto A, auto OX, auto OB, float* d, const uint32_t (&a)[4], uint64_t db) {
        if constexpr (OX.value < 0) Mma<N.value>::template rs<A.value, OB.value>(d, a, db);
        else Mma<N.value>::template ss<A.value, OX.value / 16, OB.value, 0>(d, dx, db);
    };
    auto step = [&](auto N, auto A, auto OX, auto OM, auto OO, float* d, const uint32_t (&a)[4]) {
        if constexpr (V == 0) mma(IC<72>, A, OX, IC<OM.value / 16 + (OO.value - OM.value) * 4096>, d, a, dm);
        else { mma(N, A, OX, IC<OM.value / 16>, d, a, dm); mma(IC<72 - N.value>, A, OX, IC<OO.value / 16>, d + N.value / 2, a, dt); }
    };
    float aq[36];
    auto q_steps = [&](auto LO, auto HI) {
        SFOR(i, LO.value, HI.value)
            constexpr int j = i / 4, s = i & 3;
            if (i % 12 == 0) { mbar_wait(bars + 8 * (B_FULL + 12 + i / 12)); wg_fence(); }
            step(IC<NQ>, IC<(i > 0)>, IC<-1>, IC<tile_q(j) + s * 2048>, IC<tile_q(j) + 8192 + s * 2048>, aq, xa[i]);
            if (i == Q_GO && !w) bar_arrive<2, 256>();
            if (s == 1 && j > 0 && j % 3 != 1) {
                wg_commit();
                wg_wait<1>();
                if (lead) mbar_arrive(bars + 8 * (B_EMP + 12 + (2 * j) / 3));
            }
            if ((s == 3 && j % 3 != 0) || i == HI.value - 1) wg_commit();
        SEND
    };
    {
        float acc[72], kp[20];
        const int kg = w * 8 + q * 2 + ((lane >> 3) & 1), hi = lane >> 4;
        uint32_t pk[18];
        auto stage_pk = [&](auto J) {
            constexpr int j = J.value;
            pk[j] = phi2<PHI_K>(acc[2 * j], acc[2 * j + 1]);
            const uint32_t pb = sb + OFF_PK + kg * 1152 + (lane & 7) * 16 + hi * 128;
            const uint32_t pm = pb + hh * NS * 16, pt = pb - hh * NB * 16;
            if constexpr ((j & 3) == 3) stsm4((4 * j - 4 < NB ? pm : 4 * j - 4 > NB ? pt : hi ? pt : pm) + (j / 4) * 256, pk[j - 3], pk[j - 2], pk[j - 1], pk[j]);
            if constexpr (j == 17) stsm2(pt + 1024, pk[16], pk[17]);
        };
        SFOR(st, 0, 12)
            if (st % 4 == 0) rebase(st / 4);
            mbar_wait(st ? bars + 8 * (B_FULL + st) : bars + 8 * B_F0 + ((uint32_t)(dm | dn) & (uint32_t)dz));
            if (st == 0) STAMPW(4 + w);
            SFOR(i, 0, 4) constexpr int ix = (st ? 4 * st + 4 : 0) + i; if constexpr (ix < 35) ldsm4(xa[ix], xo + slot_x(ix / 4) + (xs ^ (32 * i))); SEND
            wg_fence();
            SFOR(s, 0, (st < 9 ? 4 : v_lo(st + 1) - v_lo(st)))
                constexpr int ik = 4 * st + s, iv = v_lo(st) + s < v_lo(st + 1) ? v_lo(st) + s : -1;
                constexpr int OK = slot_k(st) + s * 2048, OV = slot_v(iv < 0 ? 0 : iv / 4) + (iv & 3) * 2048;
                constexpr int OX = slot_x(8) + 96;
                if constexpr (st < 9) {
                    if constexpr (V == 1) {
                        mma(IC<56>, IC<(ik > 0)>, IC<(ik == 35 ? OX : -1)>, IC<OK / 16>, acc, xa[ik], dm);
                        mma(IC<32>, IC<(ik > 0)>, IC<(ik == 35 ? OX : -1)>, IC<(slot_k(st) + 8192 + s * 512) / 16>, acc + 28, xa[ik], dn);
                    } else step(IC<NB>, IC<(ik > 0)>, IC<(ik == 35 ? OX : -1)>, IC<OK>, IC<OK + 8192>, acc, xa[ik]);
                }
                if constexpr (iv >= 0) {
                    if constexpr (V == 1) mma(IC<56>, IC<(iv > 0)>, IC<(iv == 35 ? OX : -1)>, IC<OV / 16>, acc + 44, xa[iv], dm);
                    else step(IC<NB>, IC<(iv > 0)>, IC<(iv == 35 ? OX : -1)>, IC<OV>, IC<OV + 8192>, acc + 36, xa[iv]);
                }
                if (s == 0 && st > 0 && st < 9) {
                    wg_commit();
                    wg_wait<1>();
                    if (lead) mbar_arrive(bars + 8 * (B_EMP + st - 1) + (st < 8 ? (xa[4 * st + 1][0] | xa[4 * st + 2][0] | xa[4 * st + 3][0]) & (uint32_t)dz : 0));
                }
                if (s == 3 && st == 0) {
                    wg_commit();
                    mbar_wait(bars + 8 * B_FULL);
                    SFOR(i, 0, 4) ldsm4(xa[4 + i], xo + slot_x(1) + (xs ^ (32 * i))); SEND
                }
            SEND
            if (st > 0) wg_commit();
            if constexpr (st >= 9) {
                constexpr int lo = st == 9 ? 0 : st == 10 ? PK_1 : PK_2, hi2 = st == 9 ? PK_1 : st == 10 ? PK_2 : 18;
                if (st == 9) {
                    wg_wait<1>();
                    if (lead) mbar_arrive(bars + 8 * (B_EMP + 8));
                    STAMPW(2 + w);
#pragma unroll
                    for (int j = 0; j < 36; j++) asm volatile("" : "+f"(acc[j]) :: "memory");
                    mbar_wait(bars + 8 * (B_EMP + 7));
                }
                SFOR(j, lo, hi2) stage_pk(IC<j>); SEND
                if (st == 11) {
                    wg_wait<1>();
                    if (lead) mbar_arrive(bars + 8 * (B_EMP + 10));
                }
            }
        SEND
        rebase(3);
        q_steps(IC<0>, IC<Q_A>);
        mbar_wait(bars + 8 * (B_EMP + 10));
        wg_wait<(Q_A > 0)>();
#pragma unroll
        for (int j = 36; j < 72; j++) asm volatile("" : "+f"(acc[j]) :: "memory");
        if (lead) mbar_arrive(bars + 8 * (B_EMP + 11));
        STAMPW(6 + w);
        {
            const uint32_t vb = sb + OFF_V + kg * 1280 + (lane & 7) * 16 + hi * 128;
            auto stage_v = [&](auto R) {
                uint32_t v[18];
#pragma unroll
                for (int i = 0; i < 18; i++) { const float* a = acc + 36 + (2 * (i + R.value) + (V == 1 ? 8 : 0)) % 36; v[i] = pack_v(a[0], a[1]); }
                const uint32_t one = 0x3F803F80u;
                stsm4(vb + 512, c < 2 ? v[8] : one, c < 2 ? v[9] : one, c < 2 ? one : v[8], c < 2 ? one : v[9]);
#pragma unroll
                for (int i = 0; i < 4; i++) { const uint32_t* a = v + 4 * i + (i >> 1) * 2; stsm4(vb + (2 * i + (i >> 1) * 2) * 128, a[0], a[1], a[2], a[3]); }
            };
            if (hh) stage_v(IC<NB / 4>); else stage_v(IC<0>);
        }
        ldsm4(xa[35], xo + slot_x(8) + (xs ^ 96));
        const uint32_t dep = xa[35][0];
        fence_async();
        bar_sync<1, 256>();
        STAMPW(8 + w);
        const uint64_t da = dz + desc(sb + OFF_PK, 1152, 128, 0) + w * 32, db = dz + desc(sb + OFF_V, 1280, 128, 0) + w * 40;
        wg_fence();
        SFOR(s, 0, 8) Mma<40>::ss<(s > 0), s * 144, s * 160, 1>(kp, da, db); SEND
        wg_commit();
        uint32_t km[2];
#pragma unroll
        for (int e = 0; e < 2; e++) {
            const uint32_t mm = q * 16 + (lane >> 2) + 8 * e - 4 * w;
            km[e] = (mm < 18 ? (w ? 0x030F0D0Du : 0x2727230Fu) : (w ? 0x7F6C6E6Eu : 0x7B7B7F7Cu)) >> (8 * c);
            if (mm >= 36) km[e] = 0u;
            asm volatile("" : "+r"(km[e]));
        }
        mbar_wait(bars + 8 * B_INIT);
        wg_fence();
        if (!QW0 || !w) q_steps(IC<Q_A>, IC<Q_B>); else wg_commit();
        wg_wait<(Q_B > Q_A)>();
        pin(kp);
        {
            char* const dst = (char*)(sc->kv + (g * 2 + w) * 384 + q * 32 + lane);
            SFOR(o, 0, 4)
                const uint32_t k = km[o >> 1];
                if (k) red4<o * 1536>(dst, k & (1 << (o & 1)) ? (k & 16 ? kp[8 + o] : kp[o]) : 0.f, k & 64 ? kp[12 + o] : kp[4 + o],
                                      k & (4 << (o & 1)) ? (k & 32 ? kp[16 + o] : kp[8 + o]) : 0.f, 1.f);
            SEND
        }
        if (lead) mbar_arrive(bars + 8 * (B_EMP + 12) + (dep & (uint32_t)dz));
        STAMPW(10 + w);
    }
    if (w) { bar_sync<2, 256>(); if (QW0) { wg_fence(); q_steps(IC<Q_A>, IC<Q_B>); } }
    wg_fence();
    q_steps(IC<Q_B>, IC<36>);
    wg_wait<0>();
    pin(aq);
    if (lead) mbar_arrive(bars + 8 * (B_EMP + 18));
    STAMPW(12 + w);
    if (!w && q < 3) load_kv(ks, sc->kv + g * 768 + q * 32 + lane);
    uint32_t t[18];
#pragma unroll
    for (int i = 0; i < 18; i++) t[i] = phi2<PHI_Q>(aq[2 * i], aq[2 * i + 1]);
#pragma unroll
    for (int i = 0; i < 18; i++) pq[i >> 2][i & 3] = hh ? t[(i + NQ / 4) % 18] : t[i];
}

template <int I, int G> __device__ __forceinline__ void load_o1(uint32_t (&a)[9][4], uint64_t p16, uint64_t p8) {
    if constexpr (I < 8) ld128<(I & 3) * 16384 + (G + I / 4) * 2048>(a[I], (const void*)p16);
    else ld64<(G + I - 8) * 1024>(a[8][2 * (I - 8)], a[8][2 * (I - 8) + 1], (const void*)p8);
}
template <int B> __device__ __forceinline__ void load_o(uint32_t (&a)[9][4], uint64_t p16, uint64_t p8) {
    SFOR(i, 0, 10) if constexpr (B > 0 || (i >= 4 && i != 8)) load_o1<i, (B == 0 ? -1 : B == 3 ? 2 : 0)>(a, p16, p8); SEND
}
template <int B> __device__ __forceinline__ uint32_t max_o(const uint32_t (&a)[9][4]) {
    uint32_t m = a[8][2];
#pragma unroll
    for (int i = B ? 0 : 4; i < (B ? 9 : 8); i++) m = max(m, a[i][0]);
    return m;
}

__global__ void __launch_bounds__(384, 1)
lab_kernel(Scratch* __restrict__ sc, const __grid_constant__ Tabs zs, const __grid_constant__ Maps mp) {
    CLK(c_entry);
    const int tid = threadIdx.x, lane = tid & 31;
    const int hh = (blockIdx.z >> 1) & 1, vv = blockIdx.y;
    const int r = (blockIdx.z & ~3) + (blockIdx.z & 1) * 2 + blockIdx.x;
    const int g = hh ? 7 - vv : vv;
    const int cb = g & 3;
    const int bid = r * 8 + g;

    const bool narrow = vv == 1;
    auto fill = [&](auto S) {
        constexpr int s = S.value;
        const int lm = (g + hh) * 64, lo = (g + 1 - hh) * 64, ck = narrow ? 128 + hh * 304 : 576 + lo;
        const uint32_t b = bars + 8 * (s ? B_FULL + s : B_F0);
        if (s == 0) { mbar_init(b, 1); tma4(sb + slot_x(0), &mp.x, 0, r * 128, 0, 0, b); pf_map(&mp.w + narrow); }
        tma4(sb + slot_k(s), &mp.w, 576 + lm, 0, 0, s, b);
        tma4(sb + slot_k(s) + 8192, &mp.w + narrow, ck, 0, narrow, s, b);
        if (s == 0) { SFOR(i, 0, 4) mbar_init(bars + 8 * (B_FULL + i), 1); SEND }
        if (s > 0) {
            tma4(sb + slot_v(s ? s - 1 : 0), &mp.w, 1152 + lm, 0, 0, s - 1, b);
            if (!narrow) tma4(sb + slot_v(s ? s - 1 : 0) + 8192, &mp.w, 1152 + lo, 0, 0, s - 1, b);
        }
        tma4(sb + slot_x(s + 1), &mp.x, 0, r * 128, 0, s + 1, bars + 8 * (B_FULL + s));
    };
    if (tid == 320) { fill(IC<0>); CLK(c_c); PUT(96, c_entry); PUT(42, c_c); }
    const int warp = __shfl_sync(0xffffffffu, tid >> 5, 0);
    if (warp >= 8) {
        asm volatile("setmaxnreg.dec.sync.aligned.u32 24;");
        if (warp != 11) {
            const bool lead = elect();
            if (warp == 10) {
                bar_arrive<0, 384>();
                if (lead) { fill(IC<1>); fill(IC<2>); fill(IC<3>); }
                if (PFLATE && lead) { pf_map(&mp.wo); pf_map(&mp.wot); pf_map(&mp.out); pf_map(&mp.outt); }
                STAMPW(41);
            } else bar_sync<0, 384>();
            if (warp == 8 && lane < 19) mbar_expect(bars + 8 * lane, zs.bytes[narrow][lane] * 256);
            bar_sync<5, 96>();
#pragma unroll 1
            for (int sid = warp - 8; sid < 5; sid += 3) {
                const uint16_t* const sp = zs.strm[g][sid];
                const CUtensorMap *ma = &mp.x + (sp[4] & 7), *mb = &mp.x + (sp[4] >> 4 & 7);
                const uint32_t ob = sp[4] >> 8 << 10, a1 = sid == 2 ? r * 128 : 0;
#pragma unroll 1
                for (uint32_t i = sp[5] & 255; i < sp[5] >> 8; i++) {
                    const uint32_t it = zs.item[i], u = sb + (it & 255) * 1024, b = bars + (it >> 5 & 248), pw = it >> 10 & 1016;
                    const int k = (it >> 20 & 15) ^ (g & it >> 24);
                    mbar_wait(bars - 8 + pw);
                    if (lead) tma4(u, ma, sp[0], a1, sp[2], k, b);
                    if (ob) { if (lead) tma4(u + ob, mb, sp[1], 0, sp[3], k, b); }
                    STAMPW(48 + i);
                }
            }
            if (lane == 0 && warp == 9) { DUMP(40, 92, 1); }
        } else {
            if (elect()) mbar_init(bars + 8 * B_INIT, 1);
            bar_arrive<0, 384>();
            char* p = (char*)sc + lane * 16;
            if (lane < 24) { st128<offsetof(Scratch, kv)>(p + bid * 768, 0u, 0u, 0u, 0u); st128<offsetof(Scratch, kv) + 384>(p + bid * 768, 0u, 0u, 0u, 0u); }
            p += bid * 18432;
            unsigned ct = clk() + SENT_0;
#pragma unroll 1
            for (uint32_t a = lane * 20; a < 7680; a += 640, p += 1536) {
                while ((int)(clk() - ct) < 0) {}
                ct += SENT_P;
                SFOR(i, 0, 3) st128<i * 512>(p, SENT, SENT, SENT, SENT); SEND
                sts128(sb + OFF_BKV + (a & ~15u), {0u, 0u, 0u, 0u});
                sts128(sb + OFF_BKV + ((a + 19) & ~15u), {0u, 0u, 0u, 0u});
            }
            GT(0);
            STAMPW(43);
            fence_async();
            __syncwarp();
            if (elect()) {
                const unsigned all = (inc_rel(&sc->init) | 127u) + 1u;
                STAMPW(44);
#pragma unroll 1
                for (int n = 0; n < SPIN_LIMIT && (int)(ld_acq(&sc->init) - all) < 0; n++) {}
                mbar_arrive(bars + 8 * B_INIT);
                STAMPW(46);
            }
        }
    } else {
        const bool lead = elect();
        if (lead) {
#pragma unroll
            for (int i = 0; i < 5; i++) mbar_init(bars + 40 + 40 * warp + 8 * i, warp < 4 ? 1 : 8);
        }
        bar_sync<0, 384>();
        asm volatile("setmaxnreg.inc.sync.aligned.u32 240;");
        const int w = warp >> 2, q = warp & 3, t = tid & 127;
        const int half = hh ^ w;
        const int c = lane & 3;
        STAMPW(0 + w);
        const uint64_t dz = zs.z;
        uint32_t pq[5][4], s[8][4];
        switch (vv) {
            case 0: front<0>(pq, s, sc, g, hh, w, q, lead, zs); break;
            case 1: front<1>(pq, s, sc, g, hh, w, q, lead, zs); break;
            case 2: front<2>(pq, s, sc, g, hh, w, q, lead, zs); break;
            default: front<3>(pq, s, sc, g, hh, w, q, lead, zs); break;
        }
        pq[4][2] = pq[4][3] = 0u;
#pragma unroll
        for (int i = 0; i < 20; i++) asm volatile("" : "+r"(pq[i >> 2][i & 3]));
        STAMPW(14 + w);
        const int t2 = fresh_tid() & 127;
        if (w == 0) {
            if (q < 3) {
                uint32_t ad[4][2];
#pragma unroll
                for (int u = 0; u < 4; u++) {
                    const uint32_t a0 = sb + OFF_BKV + q * 1152 + t2 * 4 + (u >> 1) * 3840 + (u & 1) * 640;
                    ad[u][0] = t2 >= (u == 0 ? 40 : u == 2 ? 56 : 32) ? a0 + 256 : a0;
                    ad[u][1] = u >> 1 ? (c != 3 ? a0 : ad[u][0]) : (c != 0 ? a0 + 256 : ad[u][0]);
                }
                const float need = t2 < 16 ? 96.f : t2 < 64 ? 128.f : t2 < 80 ? 64.f : 32.f;
#pragma unroll 1
                for (int n = 0; n < SPIN_LIMIT; n++) {
                    float cnt = 0.f;
#pragma unroll
                    for (int u = 0; u < 4; u++) {
                        const uint32_t(&a)[4] = s[2 * u];
                        const uint32_t(&b)[4] = s[2 * u + 1];
                        sts32(ad[u][u >> 1], pack(__uint_as_float(a[0]), __uint_as_float(b[0])));
                        sts32(ad[u][0] + 128, pack(__uint_as_float(a[1]), __uint_as_float(b[1])));
                        sts32(ad[u][1 - (u >> 1)] + 256, pack(__uint_as_float(a[2]), __uint_as_float(b[2])));
                        cnt += __uint_as_float(a[3]) + __uint_as_float(b[3]);
                    }
                    if (__all_sync(0xffffffffu, cnt == need)) break;
                    load_kv(s, sc->kv + g * 768 + t2);
                }
                STAMPW(16);
                fence_async();
            }
            bar_arrive<4, 256>();
            bar_sync<3, 128>();
        } else {
            bar_sync<4, 256>();
        }
        STAMPW(18 + w);
        uint32_t oa[4][9][4];
        const uint64_t p16 = (uint64_t)(sc->o + ((r * 2 + half) * 32 + g) * 128 + t2), p8 = (uint64_t)(sc->oh + ((r * 2 + half) * 8 + g) * 128 + t2);
        {
            float nx[20], ny[20];
            const uint64_t db = dz + desc(sb + OFF_BKV, 640, 128, 0);
            wg_fence();
            SFOR(s, 0, 3)
                Mma<40>::rs<(s > 0), s * 80>(nx, pq[s], db);
                Mma<40>::rs<(s > 0), 240 + s * 80>(ny, pq[2 + s], db);
            SEND
            wg_commit();
            wg_wait<0>();
            pin(nx); pin(ny);
#pragma unroll
            for (int e = 0; e < 2; e++) {
                const float ma = rcp((c < 2 ? ny[2 * e] : nx[16 + 2 * e]) + 1e-6f);
                const float mb = rcp((c < 2 ? ny[2 * e + 1] : nx[17 + 2 * e]) + 1e-6f);
                const float ta = __shfl_xor_sync(0xffffffffu, ma, 2), tb = __shfl_xor_sync(0xffffffffu, mb, 2);
                const float r0 = c < 2 ? ta : ma, r1 = c < 2 ? tb : mb, r2 = c < 2 ? ma : ta, r3 = c < 2 ? mb : tb;
                const float r01 = c == 0 ? r0 : r1, r23 = c == 3 ? r3 : r2, r12 = c < 2 ? tb : ta;
                const int z = 2 * e;
                oa[0][0][0 + e] = pack(nx[z] * r0, nx[z + 1] * r0);
                oa[0][0][2 + e] = pack(nx[4 + z] * r0, nx[5 + z] * r0);
                oa[0][1][0 + e] = pack(nx[8 + z] * r01, nx[9 + z] * r01);
                oa[0][1][2 + e] = pack(nx[12 + z] * r1, nx[13 + z] * r1);
                oa[0][2][0 + e] = pack((c < 2 ? nx[16 + z] : ny[z]) * r12, (c < 2 ? nx[17 + z] : ny[z + 1]) * r12);
                oa[0][2][2 + e] = pack(ny[4 + z] * r2, ny[5 + z] * r2);
                oa[0][3][0 + e] = pack(ny[8 + z] * r23, ny[9 + z] * r23);
                oa[0][3][2 + e] = pack(ny[12 + z] * r3, ny[13 + z] * r3);
                oa[0][8][e] = pack(ny[16 + z] * r3, ny[17 + z] * r3);
            }
            if (w) bar_sync<1, 256>();
            SFOR(i, 0, 4) st128<i * 16384>((void*)p16, oa[0][i][0], oa[0][i][1], oa[0][i][2], oa[0][i][3]); SEND
            st64<0>((void*)p8, oa[0][8][0], oa[0][8][1]);
        }
        STAMPW(20 + w);
        if (w) {
            const unsigned c0 = clk();
            while (clk() - c0 < DELAY_LATE) {}
            bar_arrive<2, 256>();
        } else {
            bar_arrive<1, 256>();
            const unsigned c0 = clk();
            float ao[72];
            const uint64_t db = dz + desc(sb, 9216, 1024, 1), dp = dz + desc(sb, 9216, 27648, 1);
            constexpr int NP = PIECES % 10, PC[3] = {PIECES / 10 % 10 * 32, PIECES / 100 % 10 * 32, PIECES / 1000 * 32};
            auto o_step = [&](auto P, auto I) {
                constexpr int C = PC[P.value], N = C == 64 ? 80 : NP == 2 ? 64 : 32;
                constexpr int B = I.value / 9, i = I.value % 9, O = (tile_o(2 * B + (i & 4) / 4) + C / 64 * 9216 + C % 64 * 2) / 16;
                if constexpr (i < 8) Mma<N>::template rs<(I.value > 0), O + (i & 3) * 128>(ao + C / 2, oa[B][i], db);
                else Mma<N>::template rs<1, O + 512>(ao + C / 2, oa[B][8], dp);
            };
            mbar_wait(bars + 8 * (B_FULL + 15));
            const uint64_t q16[3] = {p16 ^ 2048, (p16 ^ 4096) & ~2048ull, (p16 ^ 8192) & ~6144ull};
            const uint64_t q8[3] = {p8 ^ 1024, (p8 ^ 2048) & ~1024ull, (p8 ^ 4096) & ~3072ull};
            while (clk() - c0 < DELAY_EARLY + (vv == 0 ? DV : vv == 2 ? -DV : 0)) {}
            STAMPW(34);
            load_o<0>(oa[0], q16[0], q8[0]); load_o<1>(oa[1], q16[1], q8[1]);
            wg_fence();
            SFOR(i, 0, 4) SFOR(p, 0, NP) o_step(IC<p>, IC<i>); SEND SEND
            wg_commit();
            wg_wait<0>();
            SFOR(H, 0, 2)
                mbar_wait(bars + 8 * (B_FULL + 16 + H));
                int n = 0;
#pragma unroll 1
                for (; n < SPIN_LIMIT; n++) {
                    if ((H == 0 && !OWN_LATE) || n > 0) { load_o<2 * H>(oa[2 * H], q16[2 * H], q8[2 * H]); load_o<2 * H + 1>(oa[2 * H + 1], q16[H + 1], q8[H + 1]); }
                    if (__all_sync(0xffffffffu, max(max_o<2 * H>(oa[2 * H]), max_o<1>(oa[2 * H + 1])) != SENT)) break;
                }
                STAMPW(22 + 2 * H);
                if constexpr (H == 0) {
                    bar_sync<2, 256>();
                    load_o<2>(oa[2], q16[2], q8[2]); load_o<3>(oa[3], q16[2], q8[2]);
                    wg_fence();
                    SFOR(i, 4, 18) SFOR(p, 0, NP) o_step(IC<p>, IC<i>); SEND SEND
                    wg_commit();
                }
            SEND
            const int l2 = t2 & 31;
            const uint32_t mb = sb + q * 4096, tb = sb + 16384 + q * 512;
            const uint32_t ro = mb + (l2 & 15) * 128, sw = ((l2 >> 4) ^ (l2 & 7)) << 4;
            const uint32_t rh = mb + (l2 & 15) * 64, sh = ((l2 >> 4) ^ ((l2 >> 1) & 3)) << 4;
            int row0 = r * 128 + hh * 64 + q * 16, cl = cb * 128, ct = 512 + cb * 16;
            asm volatile("" : "+r"(row0), "+r"(cl), "+r"(ct));
            auto stage = [&](auto I) {
                constexpr int i = I.value;
                const float* a = ao + 8 * i;
                stsm4(i == 8 ? tb + (l2 & 15) * 32 + (l2 >> 4) * 16 : NP == 2 || i >= 4 ? ro + (i >> 2) * 2048 + (sw ^ (32 * (i & 3))) : rh + (i >> 1) * 1024 + (sh ^ (32 * (i & 1))),
                      pack(a[0], a[1]), pack(a[2], a[3]), pack(a[4], a[5]), pack(a[6], a[7]));
            };
            auto store = [&](auto P) {
                constexpr int C = PC[P.value];
                fence_async();
                __syncwarp();
                if (lead) {
                    tma_st2(&mp.out, mb + C * 32, cl + C, row0);
                    if (C == 64) tma_st2(&mp.outt, tb, ct, row0);
                }
            };
            wg_fence();
            SFOR(p, 0, 2) SFOR(i, 18, (p ? 18 + O_K : 36)) o_step(IC<p>, IC<i>); SEND wg_commit(); SEND
            SFOR(p, 0, NP)
                constexpr int C = PC[p], N = C == 64 ? 80 : NP == 2 ? 64 : 32;
                wg_wait<NP - 1 - p>();
                if (p == 0) bar_sync<3, 128>();
#pragma unroll
                for (int j = C / 2; j < (C + N) / 2; j++) asm volatile("" : "+f"(ao[j]) :: "memory");
                STAMPW(28 + 2 * p);
                SFOR(i, C / 16, (C + N) / 16) stage(IC<i>); SEND
                if (p == 0 && O_F) { wg_fence(); SFOR(i, 18 + O_K, 36) o_step(IC<1>, IC<i>); SEND wg_commit(); }
                store(IC<p>);
                if (p == 0 && !O_F) { wg_fence(); SFOR(i, 18 + O_K, 36) o_step(IC<1>, IC<i>); SEND wg_commit(); }
            SEND
            if (lead) {
                asm volatile("cp.async.bulk.commit_group;" ::: "memory");
                asm volatile("cp.async.bulk.wait_group.read 0;" ::: "memory");
            }
            STAMPW(32);
            GT(1);
        }
        if (t == 0) { DUMP(w, 40, 2); }
    }
}

typedef CUresult (*EncodeFn)(CUtensorMap*, CUtensorMapDataType, cuuint32_t, void*, const cuuint64_t*, const cuuint64_t*,
                             const cuuint32_t*, const cuuint32_t*, CUtensorMapInterleave, CUtensorMapSwizzle,
                             CUtensorMapL2promotion, CUtensorMapFloatOOBfill);

void encode(EncodeFn fn, CUtensorMap* m, const void* base, int rank, const cuuint64_t* dims, const cuuint64_t* strides,
            const cuuint32_t* box, CUtensorMapSwizzle sw, CUtensorMapL2promotion pr = CU_TENSOR_MAP_L2_PROMOTION_L2_128B) {
    const cuuint32_t es[4] = {1, 1, 1, 1};
    fn(m, CU_TENSOR_MAP_DATA_TYPE_BFLOAT16, rank, const_cast<void*>(base), dims, strides, box, es, CU_TENSOR_MAP_INTERLEAVE_NONE, sw,
       pr, CU_TENSOR_MAP_FLOAT_OOB_FILL_NONE);
}

}

extern "C" void kernel_launch(void* const* d_in, const int* in_sizes, int n_in, void* d_out, int out_size) {
    (void)in_sizes; (void)n_in; (void)out_size;
    static EncodeFn fn = nullptr;
    static Scratch* sc = nullptr;
    if (!fn) {
        void* p = nullptr;
        cudaDriverEntryPointQueryResult qr;
        cudaGetDriverEntryPoint("cuTensorMapEncodeTiled", &p, cudaEnableDefault, &qr);
        fn = (EncodeFn)p;
        cudaGetSymbolAddress((void**)&sc, g_scratch);
        cudaFuncSetAttribute(lab_kernel, cudaFuncAttributeMaxDynamicSharedMemorySize, SMEM_BYTES);
        cudaFuncAttributes fa; int dev = 0, res = 0;
        cudaFuncGetAttributes(&fa, lab_kernel);
        cudaGetDevice(&dev);
        cudaDeviceGetAttribute(&res, cudaDevAttrReservedSharedMemoryPerBlock, dev);
        if (fa.sharedSizeBytes != 0 || res != 1024 || ((uintptr_t)sc & 16383)) sc = nullptr;
    }
    if (!sc) return;
    const void *x = d_in[0], *wqkv = d_in[1], *wo = d_in[2];
    constexpr Tabs zs = make_tabs();
    Maps mp;
    const auto SW = CU_TENSOR_MAP_SWIZZLE_128B;
    { cuuint64_t d[4] = {64, 2048, 1, 9}, s[3] = {1152, 128, 128}; cuuint32_t b[4] = {64, 128, 1, 1}; encode(fn, &mp.x, x, 4, d, s, b, SW, XPROMO); }
    { cuuint64_t d[4] = {1728, 64, 1, 9}, s[3] = {3456, 3456, 64 * 3456}; cuuint32_t b[4] = {64, 64, 1, 1}; encode(fn, &mp.w, wqkv, 4, d, s, b, SW); }
    { cuuint64_t d[4] = {576, 64, 3, 9}, s[3] = {3456, 1152, 64 * 3456}; cuuint32_t b[4] = {16, 64, 2, 1}; encode(fn, &mp.w16, wqkv, 4, d, s, b, CU_TENSOR_MAP_SWIZZLE_32B); }
    { cuuint64_t d[4] = {64, 72, 9, 8}, s[3] = {1152, 128, 72 * 1152}; cuuint32_t b[4] = {64, 72, 2, 1}; encode(fn, &mp.wo, wo, 4, d, s, b, SW); }
    { cuuint64_t d[4] = {576, 72, 1, 8}, s[3] = {1152, 1152, 72 * 1152}; cuuint32_t b[4] = {16, 72, 1, 1}; encode(fn, &mp.wot, wo, 4, d, s, b, SW); }
    { cuuint64_t d[2] = {576, 2048}, s[1] = {1152}; cuuint32_t b[2] = {64, 16}; encode(fn, &mp.out, d_out, 2, d, s, b, SW); }
    { cuuint64_t d[2] = {576, 2048}, s[1] = {1152}; cuuint32_t b[2] = {16, 16}; encode(fn, &mp.outt, d_out, 2, d, s, b, CU_TENSOR_MAP_SWIZZLE_NONE); }
    lab_kernel<<<MAP == 2 ? dim3(2, 4, 16) : dim3(4, 4, 8), 384, SMEM_BYTES, cudaStreamPerThread>>>(sc, zs, mp);
}
```

```cpp
#include <cuda_runtime.h>
#include <cuda_bf16.h>
#include <cuda.h>
#include <stdint.h>
#include <stddef.h>
#include <type_traits>

namespace {
#define VSCH 0x433333333224ull

__host__ __device__ constexpr int slot_k(int c) { constexpr int t[4] = {150, 54, 86, 0}; return t[c & 3] * 1024; }
__host__ __device__ constexpr int slot_v(int c) { constexpr int t[9] = {118, 134, 166, 182, 118, 134, 166, 182, 198}; return t[c] * 1024; }
__host__ __device__ constexpr int slot_x(int c) { constexpr int t[5] = {18, 70, 102, 38, 198}; return t[c % 5] * 1024; }
__host__ __device__ constexpr int v_lo(int s) { int n = 0; for (int i = 0; i < s; i++) n += (int)(VSCH >> (44 - 4 * i)) & 15; return n; }
__host__ __device__ constexpr int v_step(int k) { int s = 0; while (v_lo(s + 1) <= k) s++; return s; }
constexpr int OFF_PK = 0, OFF_V = 18432;
__host__ __device__ constexpr int tile_q(int j) { return (54 + 18 * j) * 1024; }
__host__ __device__ constexpr int tile_o(int p) { return 27648 * p; }
constexpr int OFF_BKV = 218 * 1024;
static_assert(v_lo(12) == 36 && v_lo(11) >= 32 && v_lo(1) > 0, "v schedule");
constexpr int OFF_BAR = OFF_BKV + 7680;
constexpr int SMEM_BYTES = 232448;
constexpr int B_F0 = 0;
constexpr int B_FULL = 1;
constexpr int B_V1 = 19;
constexpr int B_INIT = 45;
constexpr int B_EMP = 25;
#define KV_I 5
#define AFT 1
#define SPL 2
#define Q_A 2
#define Q_B 3
#define Q_GO 35
#define SENT_0 400
#define SENT_P 140
#define PK_1 6
#define PK_2 12
#define O_K2 12
#define O_K 6
#define V8AT 5
#define DELAY_EARLY 680
#define DELAY_LATE 600
constexpr uint32_t SENT = 0xFFFFFFFFu;
constexpr int SPIN_LIMIT = 1 << 17;

struct Scratch {
    uint4 o[32 * 4 * 8 * 128];
    uint2 oh[32 * 8 * 128];
    float4 kv[8 * 2 * 4 * 96];
    unsigned init;
};
__device__ uint4 g_scratch[(sizeof(Scratch) + 16384) / 16];
#define GT(i) do {} while (0)
#define CLK(v) do {} while (0)
#define PUT(i, v) do {} while (0)
#define STAMP(i) do {} while (0)
#define STAMPW(i) do {} while (0)
#define DUMP(lo, hi, step) do {} while (0)

__device__ __forceinline__ void mbar_init(uint32_t bar, uint32_t cnt) { asm volatile("mbarrier.init.shared::cta.b64 [%0], %1;" :: "r"(bar), "r"(cnt) : "memory"); }
__device__ __forceinline__ void mbar_arrive(uint32_t bar) { asm volatile("mbarrier.arrive.shared::cta.b64 _, [%0];" :: "r"(bar) : "memory"); }
__device__ __forceinline__ void mbar_wait(uint32_t bar) {
    asm volatile("{ .reg .pred p;\n"
                 "W: mbarrier.try_wait.parity.shared::cta.b64 p, [%0], 0;\n"
                 "@!p bra.uni W; }" :: "r"(bar) : "memory");
}
__device__ __forceinline__ bool elect() {
    uint32_t p; asm volatile("{ .reg .pred q; elect.sync _|q, 0xffffffff; selp.u32 %0, 1, 0, q; }" : "=r"(p)); return p;
}
__device__ __forceinline__ void mbar_expect(uint32_t bar, uint32_t bytes) { asm volatile("mbarrier.arrive.expect_tx.shared::cta.b64 _, [%0], %1;" :: "r"(bar), "r"(bytes) : "memory"); }
__device__ __forceinline__ void tma4(uint32_t dst, const CUtensorMap* m, int c0, int c1, int c2, int c3, uint32_t bar) {
    asm volatile("cp.async.bulk.tensor.4d.shared::cluster.global.mbarrier::complete_tx::bytes [%0], [%1, {%3, %4, %5, %6}], [%2];"
                 :: "r"(dst), "l"(m), "r"(bar), "r"(c0), "r"(c1), "r"(c2), "r"(c3) : "memory");
}
__device__ __forceinline__ void tma_st2(const CUtensorMap* m, uint32_t src, int c0, int c1) {
    asm volatile("cp.async.bulk.tensor.2d.global.shared::cta.bulk_group [%0, {%2, %3}], [%1];" :: "l"(m), "r"(src), "r"(c0), "r"(c1) : "memory");
}
__device__ __forceinline__ void pf_map(const CUtensorMap* m) { asm volatile("prefetch.tensormap [%0];" :: "l"(m) : "memory"); }
__device__ __forceinline__ void fence_async() { asm volatile("fence.proxy.async.shared::cta;" ::: "memory"); }
template <int ID, int N> __device__ __forceinline__ void bar_sync() { asm volatile("bar.sync %0, %1;" :: "n"(ID), "n"(N) : "memory"); }
template <int ID, int N> __device__ __forceinline__ void bar_arrive() { asm volatile("bar.arrive %0, %1;" :: "n"(ID), "n"(N) : "memory"); }
__device__ __forceinline__ void wg_fence() { asm volatile("wgmma.fence.sync.aligned;" ::: "memory"); }
__device__ __forceinline__ void wg_commit() { asm volatile("wgmma.commit_group.sync.aligned;" ::: "memory"); }
template <int N> __device__ __forceinline__ void wg_wait() { asm volatile("wgmma.wait_group.sync.aligned %0;" :: "n"(N) : "memory"); }
template <int N> __device__ __forceinline__ void pin(float (&d)[N]) {
#pragma unroll
    for (int i = 0; i < N; i++) asm volatile("" : "+f"(d[i]) :: "memory");
}
__host__ __device__ constexpr uint64_t desc(uint32_t addr, uint32_t lbo, uint32_t sbo, uint64_t sw) {
    return (addr >> 4) | ((uint64_t)(lbo >> 4) << 16) | ((uint64_t)(sbo >> 4) << 32) | (sw << 62);
}
__device__ __forceinline__ void ldsm4(uint32_t (&r)[4], uint32_t a) {
    asm volatile("ldmatrix.sync.aligned.m8n8.x4.shared.b16 {%0,%1,%2,%3}, [%4];" : "=r"(r[0]), "=r"(r[1]), "=r"(r[2]), "=r"(r[3]) : "r"(a) : "memory");
}
__device__ __forceinline__ void stsm4(uint32_t a, uint32_t r0, uint32_t r1, uint32_t r2, uint32_t r3) {
    asm volatile("stmatrix.sync.aligned.m8n8.x4.shared.b16 [%0], {%1,%2,%3,%4};" :: "r"(a), "r"(r0), "r"(r1), "r"(r2), "r"(r3) : "memory");
}
__device__ __forceinline__ void stsm2(uint32_t a, uint32_t r0, uint32_t r1) {
    asm volatile("stmatrix.sync.aligned.m8n8.x2.shared.b16 [%0], {%1,%2};" :: "r"(a), "r"(r0), "r"(r1) : "memory");
}
__device__ __forceinline__ void sts128(uint32_t a, const uint32_t (&r)[4]) {
    asm volatile("st.shared.v4.b32 [%4], {%0,%1,%2,%3};" :: "r"(r[0]), "r"(r[1]), "r"(r[2]), "r"(r[3]), "r"(a) : "memory");
}
__device__ __forceinline__ void sts32(uint32_t a, uint32_t v) { asm volatile("st.shared.b32 [%0], %1;" :: "r"(a), "r"(v) : "memory"); }
__device__ __forceinline__ uint32_t pack(float lo, float hi) {
    uint32_t r; asm("cvt.rn.bf16x2.f32 %0, %1, %2;" : "=r"(r) : "f"(hi), "f"(lo)); return r;
}
__device__ __forceinline__ uint32_t pack_v(float lo, float hi) {
    uint32_t r; asm volatile("cvt.rn.bf16x2.f32 %0, %1, %2;" : "=r"(r) : "f"(hi), "f"(lo)); return r;
}
__device__ __forceinline__ uint32_t phi2(float lo, float hi) {
    uint32_t r;
    asm volatile("{ .reg .f32 a, b; .reg .b32 e, t;\n"
        "mul.f32 a, %1, 0f3FB8AA3B; mul.f32 b, %2, 0f3FB8AA3B; ex2.approx.ftz.f32 a, a; ex2.approx.ftz.f32 b, b;\n"
        "add.sat.f32 a, a, 0f358637BD; add.sat.f32 b, b, 0f358637BD;\n"
        "cvt.rn.bf16x2.f32 e, b, a; cvt.rn.relu.bf16x2.f32 t, %2, %1; add.rn.bf16x2 %0, e, t; }" : "=r"(r) : "f"(lo), "f"(hi));
    return r;
}
__device__ __forceinline__ float rcp(float t) { float r; asm("rcp.approx.ftz.f32 %0, %1;" : "=f"(r) : "f"(t)); return r; }
template <int OFF> __device__ __forceinline__ void st128(void* p, uint32_t a, uint32_t b, uint32_t c, uint32_t d) {
    asm volatile("{ .reg .b128 v; .reg .b64 lo, hi; mov.b64 lo, {%1,%2}; mov.b64 hi, {%3,%4}; mov.b128 v, {lo,hi};\n"
                 "st.relaxed.gpu.global.b128 [%0 + %5], v; }" :: "l"(p), "r"(a), "r"(b), "r"(c), "r"(d), "n"(OFF) : "memory");
}
template <int OFF> __device__ __forceinline__ void st64(void* p, uint32_t a, uint32_t b) {
    asm volatile("{ .reg .b64 v; mov.b64 v, {%1,%2}; st.relaxed.gpu.global.b64 [%0 + %3], v; }" :: "l"(p), "r"(a), "r"(b), "n"(OFF) : "memory");
}
template <int OFF> __device__ __forceinline__ void ld128(uint32_t (&r)[4], const void* p) {
    asm volatile("{ .reg .b128 v; .reg .b64 lo, hi; ld.relaxed.gpu.global.b128 v, [%4 + %5]; mov.b128 {lo,hi}, v;\n"
                 "mov.b64 {%0,%1}, lo; mov.b64 {%2,%3}, hi; }" : "=r"(r[0]), "=r"(r[1]), "=r"(r[2]), "=r"(r[3]) : "l"(p), "n"(OFF) : "memory");
}
template <int OFF> __device__ __forceinline__ void ld64(uint32_t& a, uint32_t& b, const void* p) {
    asm volatile("{ .reg .b64 v; ld.relaxed.gpu.global.b64 v, [%2 + %3]; mov.b64 {%0,%1}, v; }" : "=r"(a), "=r"(b) : "l"(p), "n"(OFF) : "memory");
}
__device__ __forceinline__ unsigned ld_acq(const unsigned* p) { unsigned v; asm volatile("ld.acquire.gpu.global.u32 %0, [%1];" : "=r"(v) : "l"(p) : "memory"); return v; }
__device__ __forceinline__ unsigned inc_rel(unsigned* p) { unsigned v; asm volatile("atom.release.gpu.global.add.u32 %0, [%1], 1;" : "=r"(v) : "l"(p) : "memory"); return v; }
template <int OFF> __device__ __forceinline__ void red4(void* p, float a, float b, float c, float d) {
    asm volatile("red.relaxed.gpu.global.add.v4.f32 [%0 + %5], {%1,%2,%3,%4};" :: "l"(p), "f"(a), "f"(b), "f"(c), "f"(d), "n"(OFF) : "memory");
}
__device__ __forceinline__ unsigned clk() { unsigned v; asm volatile("mov.u32 %0, %%clock;" : "=r"(v) :: "memory"); return v; }
__device__ __forceinline__ int fresh_tid() { int v; asm volatile("mov.u32 %0, %%tid.x;" : "=r"(v)); return v; }
template <int N> struct Mma;
template <> struct Mma<24> {
    template <int ACC, int OB> static __device__ __forceinline__ void rs(float* d, const uint32_t (&a)[4], uint64_t b) {
        asm volatile("{ .reg .pred p; .reg .b64 db; add.s64 db, %16, %18; setp.ne.b32 p, %17, 0;\n"
            "wgmma.mma_async.sync.aligned.m64n24k16.f32.bf16.bf16 {%0,%1,%2,%3,%4,%5,%6,%7,%8,%9,%10,%11},\n"
            "{%12,%13,%14,%15}, db, p, 1, 1, 1; }"
            : "+f"(d[0]), "+f"(d[1]), "+f"(d[2]), "+f"(d[3]), "+f"(d[4]), "+f"(d[5]), "+f"(d[6]), "+f"(d[7]), "+f"(d[8]), "+f"(d[9]), "+f"(d[10]), "+f"(d[11])
            : "r"(a[0]), "r"(a[1]), "r"(a[2]), "r"(a[3]), "l"(b), "n"(ACC), "n"(OB));
    }
    template <int ACC, int OA, int OB, int TA> static __device__ __forceinline__ void ss(float* d, uint64_t a, uint64_t b) {
        asm volatile("{ .reg .pred p; .reg .b64 da, db; add.s64 da, %12, %15; add.s64 db, %13, %16; setp.ne.b32 p, %14, 0;\n"
            "wgmma.mma_async.sync.aligned.m64n24k16.f32.bf16.bf16 {%0,%1,%2,%3,%4,%5,%6,%7,%8,%9,%10,%11},\n"
            "da, db, p, 1, 1, %17, 1; }"
            : "+f"(d[0]), "+f"(d[1]), "+f"(d[2]), "+f"(d[3]), "+f"(d[4]), "+f"(d[5]), "+f"(d[6]), "+f"(d[7]), "+f"(d[8]), "+f"(d[9]), "+f"(d[10]), "+f"(d[11])
            : "l"(a), "l"(b), "n"(ACC), "n"(OA), "n"(OB), "n"(TA));
    }
};
template <> struct Mma<32> {
    template <int ACC, int OB> static __device__ __forceinline__ void rs(float* d, const uint32_t (&a)[4], uint64_t b) {
        asm volatile("{ .reg .pred p; .reg .b64 db; add.s64 db, %20, %22; setp.ne.b32 p, %21, 0;\n"
            "wgmma.mma_async.sync.aligned.m64n32k16.f32.bf16.bf16 {%0,%1,%2,%3,%4,%5,%6,%7,%8,%9,%10,%11,%12,%13,%14,%15},\n"
            "{%16,%17,%18,%19}, db, p, 1, 1, 1; }"
            : "+f"(d[0]), "+f"(d[1]), "+f"(d[2]), "+f"(d[3]), "+f"(d[4]), "+f"(d[5]), "+f"(d[6]), "+f"(d[7]), "+f"(d[8]), "+f"(d[9]), "+f"(d[10]), "+f"(d[11]), "+f"(d[12]), "+f"(d[13]), "+f"(d[14]), "+f"(d[15])
            : "r"(a[0]), "r"(a[1]), "r"(a[2]), "r"(a[3]), "l"(b), "n"(ACC), "n"(OB));
    }
    template <int ACC, int OA, int OB, int TA> static __device__ __forceinline__ void ss(float* d, uint64_t a, uint64_t b) {
        asm volatile("{ .reg .pred p; .reg .b64 da, db; add.s64 da, %16, %19; add.s64 db, %17, %20; setp.ne.b32 p, %18, 0;\n"
            "wgmma.mma_async.sync.aligned.m64n32k16.f32.bf16.bf16 {%0,%1,%2,%3,%4,%5,%6,%7,%8,%9,%10,%11,%12,%13,%14,%15},\n"
            "da, db, p, 1, 1, %21, 1; }"
            : "+f"(d[0]), "+f"(d[1]), "+f"(d[2]), "+f"(d[3]), "+f"(d[4]), "+f"(d[5]), "+f"(d[6]), "+f"(d[7]), "+f"(d[8]), "+f"(d[9]), "+f"(d[10]), "+f"(d[11]), "+f"(d[12]), "+f"(d[13]), "+f"(d[14]), "+f"(d[15])
            : "l"(a), "l"(b), "n"(ACC), "n"(OA), "n"(OB), "n"(TA));
    }
};
template <> struct Mma<40> {
    template <int ACC, int OB> static __device__ __forceinline__ void rs(float* d, const uint32_t (&a)[4], uint64_t b) {
        asm volatile("{ .reg .pred p; .reg .b64 db; add.s64 db, %24, %26; setp.ne.b32 p, %25, 0;\n"
            "wgmma.mma_async.sync.aligned.m64n40k16.f32.bf16.bf16 {%0,%1,%2,%3,%4,%5,%6,%7,%8,%9,%10,%11,%12,%13,%14,%15,%16,%17,%18,%19},\n"
            "{%20,%21,%22,%23}, db, p, 1, 1, 1; }"
            : "+f"(d[0]), "+f"(d[1]), "+f"(d[2]), "+f"(d[3]), "+f"(d[4]), "+f"(d[5]), "+f"(d[6]), "+f"(d[7]), "+f"(d[8]), "+f"(d[9]), "+f"(d[10]), "+f"(d[11]), "+f"(d[12]), "+f"(d[13]), "+f"(d[14]), "+f"(d[15]), "+f"(d[16]), "+f"(d[17]), "+f"(d[18]), "+f"(d[19])
            : "r"(a[0]), "r"(a[1]), "r"(a[2]), "r"(a[3]), "l"(b), "n"(ACC), "n"(OB));
    }
    template <int ACC, int OA, int OB, int TA> static __device__ __forceinline__ void ss(float* d, uint64_t a, uint64_t b) {
        asm volatile("{ .reg .pred p; .reg .b64 da, db; add.s64 da, %20, %23; add.s64 db, %21, %24; setp.ne.b32 p, %22, 0;\n"
            "wgmma.mma_async.sync.aligned.m64n40k16.f32.bf16.bf16 {%0,%1,%2,%3,%4,%5,%6,%7,%8,%9,%10,%11,%12,%13,%14,%15,%16,%17,%18,%19},\n"
            "da, db, p, 1, 1, %25, 1; }"
            : "+f"(d[0]), "+f"(d[1]), "+f"(d[2]), "+f"(d[3]), "+f"(d[4]), "+f"(d[5]), "+f"(d[6]), "+f"(d[7]), "+f"(d[8]), "+f"(d[9]), "+f"(d[10]), "+f"(d[11]), "+f"(d[12]), "+f"(d[13]), "+f"(d[14]), "+f"(d[15]), "+f"(d[16]), "+f"(d[17]), "+f"(d[18]), "+f"(d[19])
            : "l"(a), "l"(b), "n"(ACC), "n"(OA), "n"(OB), "n"(TA));
    }
};
template <> struct Mma<48> {
    template <int ACC, int OB> static __device__ __forceinline__ void rs(float* d, const uint32_t (&a)[4], uint64_t b) {
        asm volatile("{ .reg .pred p; .reg .b64 db; add.s64 db, %28, %30; setp.ne.b32 p, %29, 0;\n"
            "wgmma.mma_async.sync.aligned.m64n48k16.f32.bf16.bf16 {%0,%1,%2,%3,%4,%5,%6,%7,%8,%9,%10,%11,%12,%13,%14,%15,%16,%17,%18,%19,%20,%21,%22,%23},\n"
            "{%24,%25,%26,%27}, db, p, 1, 1, 1; }"
            : "+f"(d[0]), "+f"(d[1]), "+f"(d[2]), "+f"(d[3]), "+f"(d[4]), "+f"(d[5]), "+f"(d[6]), "+f"(d[7]), "+f"(d[8]), "+f"(d[9]), "+f"(d[10]), "+f"(d[11]), "+f"(d[12]), "+f"(d[13]), "+f"(d[14]), "+f"(d[15]), "+f"(d[16]), "+f"(d[17]), "+f"(d[18]), "+f"(d[19]), "+f"(d[20]), "+f"(d[21]), "+f"(d[22]), "+f"(d[23])
            : "r"(a[0]), "r"(a[1]), "r"(a[2]), "r"(a[3]), "l"(b), "n"(ACC), "n"(OB));
    }
    template <int ACC, int OA, int OB, int TA> static __device__ __forceinline__ void ss(float* d, uint64_t a, uint64_t b) {
        asm volatile("{ .reg .pred p; .reg .b64 da, db; add.s64 da, %24, %27; add.s64 db, %25, %28; setp.ne.b32 p, %26, 0;\n"
            "wgmma.mma_async.sync.aligned.m64n48k16.f32.bf16.bf16 {%0,%1,%2,%3,%4,%5,%6,%7,%8,%9,%10,%11,%12,%13,%14,%15,%16,%17,%18,%19,%20,%21,%22,%23},\n"
            "da, db, p, 1, 1, %29, 1; }"
            : "+f"(d[0]), "+f"(d[1]), "+f"(d[2]), "+f"(d[3]), "+f"(d[4]), "+f"(d[5]), "+f"(d[6]), "+f"(d[7]), "+f"(d[8]), "+f"(d[9]), "+f"(d[10]), "+f"(d[11]), "+f"(d[12]), "+f"(d[13]), "+f"(d[14]), "+f"(d[15]), "+f"(d[16]), "+f"(d[17]), "+f"(d[18]), "+f"(d[19]), "+f"(d[20]), "+f"(d[21]), "+f"(d[22]), "+f"(d[23])
            : "l"(a), "l"(b), "n"(ACC), "n"(OA), "n"(OB), "n"(TA));
    }
};
template <> struct Mma<56> {
    template <int ACC, int OB> static __device__ __forceinline__ void rs(float* d, const uint32_t (&a)[4], uint64_t b) {
        asm volatile("{ .reg .pred p; .reg .b64 db; add.s64 db, %32, %34; setp.ne.b32 p, %33, 0;\n"
            "wgmma.mma_async.sync.aligned.m64n56k16.f32.bf16.bf16 {%0,%1,%2,%3,%4,%5,%6,%7,%8,%9,%10,%11,%12,%13,%14,%15,%16,%17,%18,%19,%20,%21,%22,%23,%24,%25,%26,%27},\n"
            "{%28,%29,%30,%31}, db, p, 1, 1, 1; }"
            : "+f"(d[0]), "+f"(d[1]), "+f"(d[2]), "+f"(d[3]), "+f"(d[4]), "+f"(d[5]), "+f"(d[6]), "+f"(d[7]), "+f"(d[8]), "+f"(d[9]), "+f"(d[10]), "+f"(d[11]), "+f"(d[12]), "+f"(d[13]), "+f"(d[14]), "+f"(d[15]), "+f"(d[16]), "+f"(d[17]), "+f"(d[18]), "+f"(d[19]), "+f"(d[20]), "+f"(d[21]), "+f"(d[22]), "+f"(d[23]), "+f"(d[24]), "+f"(d[25]), "+f"(d[26]), "+f"(d[27])
            : "r"(a[0]), "r"(a[1]), "r"(a[2]), "r"(a[3]), "l"(b), "n"(ACC), "n"(OB));
    }
    template <int ACC, int OA, int OB, int TA> static __device__ __forceinline__ void ss(float* d, uint64_t a, uint64_t b) {
        asm volatile("{ .reg .pred p; .reg .b64 da, db; add.s64 da, %28, %31; add.s64 db, %29, %32; setp.ne.b32 p, %30, 0;\n"
            "wgmma.mma_async.sync.aligned.m64n56k16.f32.bf16.bf16 {%0,%1,%2,%3,%4,%5,%6,%7,%8,%9,%10,%11,%12,%13,%14,%15,%16,%17,%18,%19,%20,%21,%22,%23,%24,%25,%26,%27},\n"
            "da, db, p, 1, 1, %33, 1; }"
            : "+f"(d[0]), "+f"(d[1]), "+f"(d[2]), "+f"(d[3]), "+f"(d[4]), "+f"(d[5]), "+f"(d[6]), "+f"(d[7]), "+f"(d[8]), "+f"(d[9]), "+f"(d[10]), "+f"(d[11]), "+f"(d[12]), "+f"(d[13]), "+f"(d[14]), "+f"(d[15]), "+f"(d[16]), "+f"(d[17]), "+f"(d[18]), "+f"(d[19]), "+f"(d[20]), "+f"(d[21]), "+f"(d[22]), "+f"(d[23]), "+f"(d[24]), "+f"(d[25]), "+f"(d[26]), "+f"(d[27])
            : "l"(a), "l"(b), "n"(ACC), "n"(OA), "n"(OB), "n"(TA));
    }
};
template <> struct Mma<64> {
    template <int ACC, int OB> static __device__ __forceinline__ void rs(float* d, const uint32_t (&a)[4], uint64_t b) {
        asm volatile("{ .reg .pred p; .reg .b64 db; add.s64 db, %36, %38; setp.ne.b32 p, %37, 0;\n"
            "wgmma.mma_async.sync.aligned.m64n64k16.f32.bf16.bf16 {%0,%1,%2,%3,%4,%5,%6,%7,%8,%9,%10,%11,%12,%13,%14,%15,%16,%17,%18,%19,%20,%21,%22,%23,%24,%25,%26,%27,%28,%29,%30,%31},\n"
            "{%32,%33,%34,%35}, db, p, 1, 1, 1; }"
            : "+f"(d[0]), "+f"(d[1]), "+f"(d[2]), "+f"(d[3]), "+f"(d[4]), "+f"(d[5]), "+f"(d[6]), "+f"(d[7]), "+f"(d[8]), "+f"(d[9]), "+f"(d[10]), "+f"(d[11]), "+f"(d[12]), "+f"(d[13]), "+f"(d[14]), "+f"(d[15]), "+f"(d[16]), "+f"(d[17]), "+f"(d[18]), "+f"(d[19]), "+f"(d[20]), "+f"(d[21]), "+f"(d[22]), "+f"(d[23]), "+f"(d[24]), "+f"(d[25]), "+f"(d[26]), "+f"(d[27]), "+f"(d[28]), "+f"(d[29]), "+f"(d[30]), "+f"(d[31])
            : "r"(a[0]), "r"(a[1]), "r"(a[2]), "r"(a[3]), "l"(b), "n"(ACC), "n"(OB));
    }
};
template <> struct Mma<72> {
    template <int ACC, int OB> static __device__ __forceinline__ void rs(float* d, const uint32_t (&a)[4], uint64_t b) {
        asm volatile("{ .reg .pred p; .reg .b64 db; add.s64 db, %40, %42; setp.ne.b32 p, %41, 0;\n"
            "wgmma.mma_async.sync.aligned.m64n72k16.f32.bf16.bf16 {%0,%1,%2,%3,%4,%5,%6,%7,%8,%9,%10,%11,%12,%13,%14,%15,%16,%17,%18,%19,%20,%21,%22,%23,%24,%25,%26,%27,%28,%29,%30,%31,%32,%33,%34,%35},\n"
            "{%36,%37,%38,%39}, db, p, 1, 1, 1; }"
            : "+f"(d[0]), "+f"(d[1]), "+f"(d[2]), "+f"(d[3]), "+f"(d[4]), "+f"(d[5]), "+f"(d[6]), "+f"(d[7]), "+f"(d[8]), "+f"(d[9]), "+f"(d[10]), "+f"(d[11]), "+f"(d[12]), "+f"(d[13]), "+f"(d[14]), "+f"(d[15]), "+f"(d[16]), "+f"(d[17]), "+f"(d[18]), "+f"(d[19]), "+f"(d[20]), "+f"(d[21]), "+f"(d[22]), "+f"(d[23]), "+f"(d[24]), "+f"(d[25]), "+f"(d[26]), "+f"(d[27]), "+f"(d[28]), "+f"(d[29]), "+f"(d[30]), "+f"(d[31]), "+f"(d[32]), "+f"(d[33]), "+f"(d[34]), "+f"(d[35])
            : "r"(a[0]), "r"(a[1]), "r"(a[2]), "r"(a[3]), "l"(b), "n"(ACC), "n"(OB));
    }
    template <int ACC, int OA, int OB, int TA> static __device__ __forceinline__ void ss(float* d, uint64_t a, uint64_t b) {
        asm volatile("{ .reg .pred p; .reg .b64 da, db; add.s64 da, %36, %39; add.s64 db, %37, %40; setp.ne.b32 p, %38, 0;\n"
            "wgmma.mma_async.sync.aligned.m64n72k16.f32.bf16.bf16 {%0,%1,%2,%3,%4,%5,%6,%7,%8,%9,%10,%11,%12,%13,%14,%15,%16,%17,%18,%19,%20,%21,%22,%23,%24,%25,%26,%27,%28,%29,%30,%31,%32,%33,%34,%35},\n"
            "da, db, p, 1, 1, %41, 1; }"
            : "+f"(d[0]), "+f"(d[1]), "+f"(d[2]), "+f"(d[3]), "+f"(d[4]), "+f"(d[5]), "+f"(d[6]), "+f"(d[7]), "+f"(d[8]), "+f"(d[9]), "+f"(d[10]), "+f"(d[11]), "+f"(d[12]), "+f"(d[13]), "+f"(d[14]), "+f"(d[15]), "+f"(d[16]), "+f"(d[17]), "+f"(d[18]), "+f"(d[19]), "+f"(d[20]), "+f"(d[21]), "+f"(d[22]), "+f"(d[23]), "+f"(d[24]), "+f"(d[25]), "+f"(d[26]), "+f"(d[27]), "+f"(d[28]), "+f"(d[29]), "+f"(d[30]), "+f"(d[31]), "+f"(d[32]), "+f"(d[33]), "+f"(d[34]), "+f"(d[35])
            : "l"(a), "l"(b), "n"(ACC), "n"(OA), "n"(OB), "n"(TA));
    }
};
template <> struct Mma<80> {
    template <int ACC, int OB> static __device__ __forceinline__ void rs(float* d, const uint32_t (&a)[4], uint64_t b) {
        asm volatile("{ .reg .pred p; .reg .b64 db; add.s64 db, %44, %46; setp.ne.b32 p, %45, 0;\n"
            "wgmma.mma_async.sync.aligned.m64n80k16.f32.bf16.bf16 {%0,%1,%2,%3,%4,%5,%6,%7,%8,%9,%10,%11,%12,%13,%14,%15,%16,%17,%18,%19,%20,%21,%22,%23,%24,%25,%26,%27,%28,%29,%30,%31,%32,%33,%34,%35,%36,%37,%38,%39},\n"
            "{%40,%41,%42,%43}, db, p, 1, 1, 1; }"
            : "+f"(d[0]), "+f"(d[1]), "+f"(d[2]), "+f"(d[3]), "+f"(d[4]), "+f"(d[5]), "+f"(d[6]), "+f"(d[7]), "+f"(d[8]), "+f"(d[9]), "+f"(d[10]), "+f"(d[11]), "+f"(d[12]), "+f"(d[13]), "+f"(d[14]), "+f"(d[15]), "+f"(d[16]), "+f"(d[17]), "+f"(d[18]), "+f"(d[19]), "+f"(d[20]), "+f"(d[21]), "+f"(d[22]), "+f"(d[23]), "+f"(d[24]), "+f"(d[25]), "+f"(d[26]), "+f"(d[27]), "+f"(d[28]), "+f"(d[29]), "+f"(d[30]), "+f"(d[31]), "+f"(d[32]), "+f"(d[33]), "+f"(d[34]), "+f"(d[35]), "+f"(d[36]), "+f"(d[37]), "+f"(d[38]), "+f"(d[39])
            : "r"(a[0]), "r"(a[1]), "r"(a[2]), "r"(a[3]), "l"(b), "n"(ACC), "n"(OB));
    }
};

template <int I, int N, class F> __device__ __forceinline__ void static_for(F&& f) {
    if constexpr (I < N) { f(std::integral_constant<int, I>{}); static_for<I + 1, N>(f); }
}
#define SFOR(var, lo, hi) static_for<lo, hi>([&](auto var##_c) { constexpr int var = decltype(var##_c)::value;
#define SEND });
template <int N> constexpr std::integral_constant<int, N> IC{};

struct __align__(64) Tabs {
    uint64_t d[4][2][4][2];
    uint64_t n[4], z;
    uint32_t item[42];
    uint16_t strm[8][5][6];
    uint16_t bytes[2][20];
};
struct Maps { CUtensorMap x, w, w16, wo, wot, out, outt; };
constexpr uint32_t sb = 1024, bars = sb + OFF_BAR;

constexpr Tabs make_tabs() {
    Tabs zs = {};
    for (int g = 0; g < 8; g++) {
        const int hh = g >> 2, cb = g & 3, lm = (g + hh) * 64, lo = (g + 1 - hh) * 64, nar = g == 1 || g == 6;
        const int crs = nar || g == 2 || g == 5, lq = crs ? g * 64 + (g == 5 ? 32 : 48) : lo;
        for (int i = 0; i < 4; i++) {
            uint64_t* d = zs.d[hh ? 7 - g : g][hh][i];
            const bool cross = crs && i == 3;
            d[0] = desc(sb, 0, 1024, 1) + (g == 7 ? 7 << 16 : hh ? 2 * cross : g);
            d[1] = desc(sb, 0, 1024, 1) + (cross ? g == 5 : hh ? g : 0);
            zs.n[i] = desc(sb, 2048, 256, 3);
        }
        const int st[5][6] = {{576 + lm, nar ? 128 + hh * 304 : 576 + lo, 0, nar, 1 | (1 + nar) << 4 | 8 << 8, 3 | 8 << 8},
                              {1152 + lm, 1152 + lo, 0, 0, 1 | 1 << 4 | (nar ? 0 : 8) << 8, 12 | 17 << 8},
                              {0, 0, 0, 0, 0, 21 | 25 << 8},
                              {lm, lq, 0, 0, 1 | 1 << 4 | 8 << 8, 25 | 34 << 8},
                              {0, 512 + cb * 16, cb * 2, 0, 3 | 4 << 4 | 18 << 8, 34 | 42 << 8}};
        for (int i = 0; i < 30; i++) zs.strm[g][i / 6][i % 6] = st[i / 6][i % 6];
    }
    auto item = [](int dst, int full, int wait, int k, int gm) constexpr { return dst / 1024 | (B_FULL + full) << 8 | (wait + 1) << 13 | k << 20 | gm << 24; };
    auto done = [](int c) constexpr { const int s = v_step(4 * c + 3); return s > 8 ? 11 : s; };
    auto mx = [](int a, int b) constexpr { return a > b ? a : b; };
    auto mn = [](int a, int b) constexpr { return a < b ? a : b; };
    auto freed = [&](int at, int n) constexpr {
        int s = 0;
        for (int c = 0; c < 9; c++) {
            if (slot_k(c) < at + n && at < slot_k(c) + 16384) s = mx(s, c);
            if (slot_v(c) < at + n && at < slot_v(c) + 16384) s = mx(s, done(c));
            if (slot_x(c) < at + n && at < slot_x(c) + 16384) s = mx(s, c - 1);
        }
        return s;
    };
    for (int c = 0; c < 9; c++) {
        if (c) zs.item[c - 1] = item(slot_k(c), c, c < 4 ? -1 : B_EMP + c - 4, c, 0);
        zs.item[8 + c] = item(slot_v(c), c == 1 && SPL > 1 ? B_V1 - B_FULL : c < 4 ? c : mn(v_step(4 * c), 9), c < 4 ? -1 : B_EMP + (c < 8 ? done(c - 4) : mx(V8AT, done(3))), c, 0);
        if (c) zs.item[16 + c] = item(slot_x(c), c - 1, c < 5 ? -1 : B_EMP + (c < 6 ? 0 : c - 6), c, 0);
        zs.item[25 + c] = item(tile_q(c), 12 + c / 3, B_EMP + freed(tile_q(c), 16384), c, 0);
        if (c < 8) zs.item[34 + c] = item(tile_o(c), 15 + (c < 4 ? c / 2 : 2), B_EMP + (c < 1 ? 12 : c + 11), c, c < 2 ? 7 : c < 4 ? 6 : 4);
    }
    for (int nar = 0; nar < 2; nar++) {
        zs.bytes[nar][B_F0] = 128 - 16 * nar;
        for (int i = 0; i < 42; i++) zs.bytes[nar][zs.item[i] >> 8 & 31] += i < 8 ? 64 - 16 * nar : i < 17 ? 64 - 32 * nar : i < 34 ? 64 : 81;
    }
    return zs;
}

__device__ __forceinline__ void load_kv(uint32_t (&s)[8][4], const void* p) { SFOR(u, 0, 8) ld128<u * 1536>(s[u], p); SEND }

template <int V>
__device__ __forceinline__ void front(uint32_t (&pq)[5][4], uint32_t (&ks)[8][4], Scratch* sc, int g, int hh, int w, int q, bool lead, const Tabs& zs) {
    const uint64_t dz = zs.z;
    constexpr int NQ = V == 1 ? 40 : V == 2 ? 32 : 64 - 8 * V, NB = 64 - 8 * V, NS = 72 - NB;
    const int lane = threadIdx.x & 31, c = lane & 3, half = hh ^ w;
    const uint32_t xo = sb + (half * 64 + q * 16 + (lane & 15)) * 128, xs = ((lane >> 4) ^ (lane & 7)) << 4;
    const uint64_t dx = dz + desc(sb, 16, 1024, 1) + half * 512;
    uint64_t dm, dt, dn;
    auto rebase = [&](int i) { dm = zs.d[V][hh][i][0]; dt = zs.d[V][hh][i][1]; dn = zs.n[i]; };
    uint32_t xa[36][4];
    auto mma = [&](auto N, auto A, auto OX, auto OB, float* d, const uint32_t (&a)[4], uint64_t db) {
        if constexpr (OX.value < 0) Mma<N.value>::template rs<A.value, OB.value>(d, a, db);
        else Mma<N.value>::template ss<A.value, OX.value / 16, OB.value, 0>(d, dx, db);
    };
    auto step = [&](auto N, auto A, auto OX, auto OM, auto OO, float* d, const uint32_t (&a)[4]) {
        if constexpr (V == 0) mma(IC<72>, A, OX, IC<OM.value / 16 + (OO.value - OM.value) * 4096>, d, a, dm);
        else { mma(N, A, OX, IC<OM.value / 16>, d, a, dm); mma(IC<72 - N.value>, A, OX, IC<OO.value / 16>, d + N.value / 2, a, dt); }
    };
    float aq[36];
    auto q_steps = [&](auto LO, auto HI) {
        SFOR(i, LO.value, HI.value)
            constexpr int j = i / 4, s = i & 3;
            if (i % 12 == 0) { if (i) mbar_wait(bars + 8 * (B_FULL + 12 + i / 12)); wg_fence(); }
            step(IC<NQ>, IC<(i > 0)>, IC<-1>, IC<tile_q(j) + s * 2048>, IC<tile_q(j) + 8192 + s * 2048>, aq, xa[i]);
            if (i == Q_GO && !w) bar_arrive<2, 256>();
            if (s == 1 && j > 0 && j % 3 != 1) {
                wg_commit();
                wg_wait<1>();
                if (lead) mbar_arrive(bars + 8 * (B_EMP + 12 + (2 * j) / 3));
            }
            if ((s == 3 && j % 3 != 0) || i == HI.value - 1) wg_commit();
        SEND
    };
    {
        float acc[72], kp[20];
        const int kg = w * 8 + q * 2 + ((lane >> 3) & 1), hi = lane >> 4;
        uint32_t pk[18];
        auto stage_pk = [&](auto J) {
            constexpr int j = J.value;
            pk[j] = phi2(acc[2 * j], acc[2 * j + 1]);
            const uint32_t pb = sb + OFF_PK + kg * 1152 + (lane & 7) * 16 + hi * 128;
            const uint32_t pm = pb + hh * NS * 16, pt = pb - hh * NB * 16;
            if constexpr ((j & 3) == 3) stsm4((4 * j - 4 < NB ? pm : 4 * j - 4 > NB ? pt : hi ? pt : pm) + (j / 4) * 256, pk[j - 3], pk[j - 2], pk[j - 1], pk[j]);
            if constexpr (j == 17) stsm2(pt + 1024, pk[16], pk[17]);
        };
        SFOR(st, 0, 12)
            if (st % 4 == 0) rebase(st / 4);
            if (st < 10) mbar_wait(st ? bars + 8 * (B_FULL + st) : bars + 8 * B_F0 + ((uint32_t)(dm | dn) & (uint32_t)dz));
            if (st == 11 && !AFT) mbar_wait(bars + 8 * (B_FULL + 12));
            if (st == 0) STAMPW(4 + w);
            SFOR(i, 0, 4) constexpr int ix = (st ? 4 * st + 4 : 0) + i; if constexpr (ix < 35) ldsm4(xa[ix], xo + slot_x(ix / 4) + (xs ^ (32 * i))); SEND
            wg_fence();
            SFOR(s, 0, (st < 9 ? 4 : v_lo(st + 1) - v_lo(st)))
                constexpr int ik = 4 * st + s, iv = st >= SPL && v_lo(st) + s < v_lo(st + 1) ? v_lo(st) + s : -1;
                constexpr int OK = slot_k(st) + s * 2048, OV = slot_v(iv < 0 ? 0 : iv / 4) + (iv & 3) * 2048;
                constexpr int OX = slot_x(8) + 96;
                if constexpr (st < 9) {
                    if constexpr (V == 1) {
                        mma(IC<56>, IC<(ik > 0)>, IC<(ik == 35 ? OX : -1)>, IC<OK / 16>, acc, xa[ik], dm);
                        mma(IC<32>, IC<(ik > 0)>, IC<(ik == 35 ? OX : -1)>, IC<(slot_k(st) + 8192 + s * 512) / 16>, acc + 28, xa[ik], dn);
                    } else step(IC<NB>, IC<(ik > 0)>, IC<(ik == 35 ? OX : -1)>, IC<OK>, IC<OK + 8192>, acc, xa[ik]);
                }
                if constexpr (iv >= 0) {
                    if constexpr (V == 1) mma(IC<56>, IC<(iv > 0)>, IC<(iv == 35 ? OX : -1)>, IC<OV / 16>, acc + 44, xa[iv], dm);
                    else step(IC<NB>, IC<(iv > 0)>, IC<(iv == 35 ? OX : -1)>, IC<OV>, IC<OV + 8192>, acc + 36, xa[iv]);
                }
                if (s == (st < SPL) && st > 0 && st < 9) {
                    wg_commit();
                    wg_wait<1>();
                    if (lead) mbar_arrive(bars + 8 * (B_EMP + st - 1) + (st < 8 ? (xa[4 * st + 1][0] | xa[4 * st + 2][0] | xa[4 * st + 3][0]) & (uint32_t)dz : 0));
                }
                if constexpr (s == 3 && st < SPL) {
                    wg_commit();
                    mbar_wait(bars + 8 * (st ? B_V1 : B_FULL));
                    if (st == 0) { SFOR(i, 0, 4) ldsm4(xa[4 + i], xo + slot_x(1) + (xs ^ (32 * i))); SEND }
                    wg_fence();
                    SFOR(i, v_lo(st), v_lo(st + 1))
                        constexpr int O0 = slot_v(i / 4) + (i & 3) * 2048;
                        if constexpr (V == 1) mma(IC<56>, IC<(i > 0)>, IC<-1>, IC<O0 / 16>, acc + 44, xa[i], dm);
                        else step(IC<NB>, IC<(i > 0)>, IC<-1>, IC<O0>, IC<O0 + 8192>, acc + 36, xa[i]);
                    SEND
                }
            SEND
            wg_commit();
            if constexpr (st >= 9) {
                constexpr int lo = st == 9 ? 0 : st == 10 ? PK_1 : PK_2, hi2 = st == 9 ? PK_1 : st == 10 ? PK_2 : 18;
                if (st == 9) {
                    mbar_wait(bars + 8 * (B_EMP + 7));
                    wg_wait<1>();
                    if (lead) mbar_arrive(bars + 8 * (B_EMP + 8));
                    STAMPW(2 + w);
#pragma unroll
                    for (int j = 0; j < 36; j++) asm volatile("" : "+f"(acc[j]) :: "memory");
                }
                if (st == 11 && AFT) mbar_wait(bars + 8 * (B_FULL + 12));
                SFOR(j, lo, hi2) stage_pk(IC<j>); SEND
            }
        SEND
        rebase(3);
        q_steps(IC<0>, IC<Q_A>);
        wg_wait<(Q_A > 0)>();
#pragma unroll
        for (int j = 36; j < 72; j++) asm volatile("" : "+f"(acc[j]) :: "memory");
        if (lead) mbar_arrive(bars + 8 * (B_EMP + 11));
        STAMPW(6 + w);
        {
            const uint32_t vb = sb + OFF_V + kg * 1280 + (lane & 7) * 16 + hi * 128;
            auto stage_v = [&](auto R) {
                uint32_t v[18];
#pragma unroll
                for (int i = 0; i < 18; i++) { const float* a = acc + 36 + (2 * (i + R.value) + (V == 1 ? 8 : 0)) % 36; v[i] = pack_v(a[0], a[1]); }
                const uint32_t one = 0x3F803F80u;
                stsm4(vb + 512, c < 2 ? v[8] : one, c < 2 ? v[9] : one, c < 2 ? one : v[8], c < 2 ? one : v[9]);
#pragma unroll
                for (int i = 0; i < 4; i++) { const uint32_t* a = v + 4 * i + (i >> 1) * 2; stsm4(vb + (2 * i + (i >> 1) * 2) * 128, a[0], a[1], a[2], a[3]); }
            };
            if (hh) stage_v(IC<NB / 4>); else stage_v(IC<0>);
        }
        ldsm4(xa[35], xo + slot_x(8) + (xs ^ 96));
        const uint32_t dep = xa[35][0];
        fence_async();
        bar_sync<1, 256>();
        STAMPW(8 + w);
        const uint64_t da = dz + desc(sb + OFF_PK, 1152, 128, 0) + w * 32, db = dz + desc(sb + OFF_V, 1280, 128, 0) + w * 40;
        wg_fence();
        SFOR(s, 0, 8) Mma<40>::ss<(s > 0), s * 144, s * 160, 1>(kp, da, db); SEND
        wg_commit();
        uint32_t km[2];
#pragma unroll
        for (int e = 0; e < 2; e++) {
            const uint32_t mm = q * 16 + (lane >> 2) + 8 * e - 4 * w;
            km[e] = (mm < 18 ? (w ? 0x030F0D0Du : 0x2727230Fu) : (w ? 0x7F6C6E6Eu : 0x7B7B7F7Cu)) >> (8 * c);
            if (mm >= 36) km[e] = 0u;
            asm volatile("" : "+r"(km[e]));
        }
        mbar_wait(bars + 8 * B_INIT);
        wg_fence();
        q_steps(IC<Q_A>, IC<Q_B>);
        wg_wait<(Q_B > Q_A)>();
        pin(kp);
        {
            char* const dst = (char*)(sc->kv + (g * 2 + w) * 384 + q * 32 + lane);
            SFOR(o, 0, 4)
                const uint32_t k = km[o >> 1];
                if (k) red4<o * 1536>(dst, k & (1 << (o & 1)) ? (k & 16 ? kp[8 + o] : kp[o]) : 0.f, k & 64 ? kp[12 + o] : kp[4 + o],
                                      k & (4 << (o & 1)) ? (k & 32 ? kp[16 + o] : kp[8 + o]) : 0.f, 1.f);
            SEND
        }
        if (lead) mbar_arrive(bars + 8 * (B_EMP + 12) + (dep & (uint32_t)dz));
        STAMPW(10 + w);
    }
    if (w) bar_sync<2, 256>();
    wg_fence();
    q_steps(IC<Q_B>, IC<36>);
    wg_wait<0>();
    pin(aq);
    if (lead) mbar_arrive(bars + 8 * (B_EMP + 18));
    STAMPW(12 + w);
    uint32_t t[18];
#pragma unroll
    for (int i = 0; i < 18; i++) {
        if (i == KV_I && !w && q < 3) {
            uint32_t dep = 0;
#pragma unroll
            for (int j = 0; j < KV_I; j++) dep |= t[j];
            load_kv(ks, sc->kv + g * 768 + q * 32 + lane + (dep & (uint32_t)dz));
        }
        t[i] = phi2(aq[2 * i], aq[2 * i + 1]);
    }
#pragma unroll
    for (int i = 0; i < 18; i++) pq[i >> 2][i & 3] = hh ? t[(i + NQ / 4) % 18] : t[i];
}

template <int I, int G> __device__ __forceinline__ void load_o1(uint32_t (&a)[9][4], uint64_t p16, uint64_t p8) {
    if constexpr (I < 8) ld128<(I & 3) * 16384 + (G + I / 4) * 2048>(a[I], (const void*)p16);
    else ld64<(G + I - 8) * 1024>(a[8][2 * (I - 8)], a[8][2 * (I - 8) + 1], (const void*)p8);
}
template <int B> __device__ __forceinline__ void load_o(uint32_t (&a)[9][4], uint64_t p16, uint64_t p8) {
    SFOR(i, 0, 10) if constexpr (B > 0 || (i >= 4 && i != 8)) load_o1<i, (B == 0 ? -1 : B == 3 ? 2 : 0)>(a, p16, p8); SEND
}
template <int B> __device__ __forceinline__ uint32_t max_o(const uint32_t (&a)[9][4]) {
    uint32_t m = a[8][2];
#pragma unroll
    for (int i = B ? 0 : 4; i < (B ? 9 : 8); i++) m = max(m, a[i][0]);
    return m;
}

__global__ void __launch_bounds__(384, 1)
lab_kernel(Scratch* __restrict__ sc, const __grid_constant__ Tabs zs, const __grid_constant__ Maps mp) {
    CLK(c_entry);
    const int tid = threadIdx.x, lane = tid & 31;
    const int hh = (blockIdx.z >> 1) & 1, vv = blockIdx.y;
    const int r = (blockIdx.z & ~3) + (blockIdx.z & 1) * 2 + blockIdx.x;
    const int g = hh ? 7 - vv : vv;
    const int cb = g & 3;
    const int bid = r * 8 + g;

    const bool narrow = vv == 1;
    auto fill = [&](auto S) {
        constexpr int s = S.value;
        const int lm = (g + hh) * 64, lo = (g + 1 - hh) * 64, ck = narrow ? 128 + hh * 304 : 576 + lo;
        const uint32_t b = bars + 8 * (s ? B_FULL + s : B_F0);
        if (s == 0) { mbar_init(b, 1); tma4(sb + slot_x(0), &mp.x, 0, r * 128, 0, 0, b); pf_map(&mp.w + narrow); }
        tma4(sb + slot_k(s), &mp.w, 576 + lm, 0, 0, s, b);
        tma4(sb + slot_k(s) + 8192, &mp.w + narrow, ck, 0, narrow, s, b);
        if (s == 0) { SFOR(i, 0, 4) mbar_init(bars + 8 * (B_FULL + i), 1); SEND mbar_init(bars + 8 * B_V1, 1); }
        const uint32_t bv = bars + 8 * (s == 1 && SPL > 1 ? B_V1 : B_FULL + s);
        if (s > 0) tma4(sb + slot_x(s + 1), &mp.x, 0, r * 128, 0, s + 1, b);
        tma4(sb + slot_v(s), &mp.w, 1152 + lm, 0, 0, s, bv);
        if (!narrow) tma4(sb + slot_v(s) + 8192, &mp.w, 1152 + lo, 0, 0, s, bv);
        if (s == 0) tma4(sb + slot_x(1), &mp.x, 0, r * 128, 0, 1, bv);
    };
    if (tid == 320) { fill(IC<0>); CLK(c_c); PUT(96, c_entry); PUT(42, c_c); }
    const int warp = __shfl_sync(0xffffffffu, tid >> 5, 0);
    if (warp >= 8) {
        asm volatile("setmaxnreg.dec.sync.aligned.u32 24;");
        if (warp != 11) {
            const bool lead = elect();
            if (warp == 10) {
                bar_arrive<0, 384>();
                if (lead) { fill(IC<1>); fill(IC<2>); fill(IC<3>); }
                STAMPW(41);
            } else bar_sync<0, 384>();
            if (warp == 8 && lane < 20) mbar_expect(bars + 8 * lane, zs.bytes[narrow][lane] * 256);
            bar_sync<5, 96>();
#pragma unroll 1
            for (int sid = warp - 8; sid < 5; sid += 3) {
                const uint16_t* const sp = zs.strm[g][sid];
                const CUtensorMap *ma = &mp.x + (sp[4] & 7), *mb = &mp.x + (sp[4] >> 4 & 7);
                const uint32_t ob = sp[4] >> 8 << 10, a1 = sid == 2 ? r * 128 : 0;
#pragma unroll 1
                for (uint32_t i = sp[5] & 255; i < sp[5] >> 8; i++) {
                    const uint32_t it = zs.item[i], u = sb + (it & 255) * 1024, b = bars + (it >> 5 & 248), pw = it >> 10 & 1016;
                    const int k = (it >> 20 & 15) ^ (g & it >> 24);
                    mbar_wait(bars - 8 + pw);
                    if (lead) tma4(u, ma, sp[0], a1, sp[2], k, b);
                    if (ob) { if (lead) tma4(u + ob, mb, sp[1], 0, sp[3], k, b); }
                    STAMPW(48 + i);
                }
            }
            if (lane == 0 && warp == 9) { DUMP(40, 92, 1); }
        } else {
            if (elect()) mbar_init(bars + 8 * B_INIT, 1);
            bar_arrive<0, 384>();
            char* p = (char*)sc + lane * 16;
            if (lane < 24) { st128<offsetof(Scratch, kv)>(p + bid * 768, 0u, 0u, 0u, 0u); st128<offsetof(Scratch, kv) + 384>(p + bid * 768, 0u, 0u, 0u, 0u); }
            p += bid * 18432;
            unsigned ct = clk() + SENT_0;
#pragma unroll 1
            for (uint32_t a = lane * 20; a < 7680; a += 640, p += 1536) {
                while ((int)(clk() - ct) < 0) {}
                ct += SENT_P;
                SFOR(i, 0, 3) st128<i * 512>(p, SENT, SENT, SENT, SENT); SEND
                sts128(sb + OFF_BKV + (a & ~15u), {0u, 0u, 0u, 0u});
                sts128(sb + OFF_BKV + ((a + 19) & ~15u), {0u, 0u, 0u, 0u});
            }
            STAMPW(43);
            fence_async();
            __syncwarp();
            if (elect()) {
                const unsigned all = (inc_rel(&sc->init) | 127u) + 1u;
                STAMPW(44);
#pragma unroll 1
                for (int n = 0; n < SPIN_LIMIT && (int)(ld_acq(&sc->init) - all) < 0; n++) {}
                mbar_arrive(bars + 8 * B_INIT);
                STAMPW(46);
            }
        }
    } else {
        const bool lead = elect();
        if (lead) {
#pragma unroll
            for (int i = 0; i < 5; i++) if (i < 4 || warp != 2) mbar_init(bars + 40 + 40 * warp + 8 * i, warp < 4 ? 1 : 8);
        }
        bar_sync<0, 384>();
        asm volatile("setmaxnreg.inc.sync.aligned.u32 240;");
        const int w = warp >> 2, q = warp & 3, t = tid & 127;
        const int half = hh ^ w;
        const int c = lane & 3;
        STAMPW(0 + w);
        const uint64_t dz = zs.z;
        uint32_t pq[5][4], s[8][4];
        switch (vv) {
            case 0: front<0>(pq, s, sc, g, hh, w, q, lead, zs); break;
            case 1: front<1>(pq, s, sc, g, hh, w, q, lead, zs); break;
            case 2: front<2>(pq, s, sc, g, hh, w, q, lead, zs); break;
            default: front<3>(pq, s, sc, g, hh, w, q, lead, zs); break;
        }
        pq[4][2] = pq[4][3] = 0u;
#pragma unroll
        for (int i = 0; i < 20; i++) asm volatile("" : "+r"(pq[i >> 2][i & 3]));
        STAMPW(14 + w);
        const int t2 = fresh_tid() & 127;
        if (w == 0) {
            if (q < 3) {
                uint32_t ad[4][2];
#pragma unroll
                for (int u = 0; u < 4; u++) {
                    const uint32_t a0 = sb + OFF_BKV + q * 1152 + t2 * 4 + (u >> 1) * 3840 + (u & 1) * 640;
                    ad[u][0] = t2 >= (u == 0 ? 40 : u == 2 ? 56 : 32) ? a0 + 256 : a0;
                    ad[u][1] = u >> 1 ? (c != 3 ? a0 : ad[u][0]) : (c != 0 ? a0 + 256 : ad[u][0]);
                }
                const float need = t2 < 16 ? 96.f : t2 < 64 ? 128.f : t2 < 80 ? 64.f : 32.f;
#pragma unroll 1
                for (int n = 0; n < SPIN_LIMIT; n++) {
                    float cnt = 0.f;
#pragma unroll
                    for (int u = 0; u < 4; u++) {
                        const uint32_t(&a)[4] = s[2 * u];
                        const uint32_t(&b)[4] = s[2 * u + 1];
                        sts32(ad[u][u >> 1], pack(__uint_as_float(a[0]), __uint_as_float(b[0])));
                        sts32(ad[u][0] + 128, pack(__uint_as_float(a[1]), __uint_as_float(b[1])));
                        sts32(ad[u][1 - (u >> 1)] + 256, pack(__uint_as_float(a[2]), __uint_as_float(b[2])));
                        cnt += __uint_as_float(a[3]) + __uint_as_float(b[3]);
                    }
                    if (__all_sync(0xffffffffu, cnt == need)) break;
                    load_kv(s, sc->kv + g * 768 + t2);
                }
                STAMPW(16);
                fence_async();
            }
            bar_arrive<4, 256>();
            bar_sync<3, 128>();
        } else {
            bar_sync<4, 256>();
        }
        STAMPW(18 + w);
        uint32_t oa[4][9][4];
        const uint64_t p16 = (uint64_t)(sc->o + ((r * 2 + half) * 32 + g) * 128 + t2), p8 = (uint64_t)(sc->oh + ((r * 2 + half) * 8 + g) * 128 + t2);
        {
            float nx[20], ny[20];
            const uint64_t db = dz + desc(sb + OFF_BKV, 640, 128, 0);
            wg_fence();
            SFOR(s, 0, 3)
                Mma<40>::rs<(s > 0), s * 80>(nx, pq[s], db);
                Mma<40>::rs<(s > 0), 240 + s * 80>(ny, pq[2 + s], db);
            SEND
            wg_commit();
            wg_wait<0>();
            pin(nx); pin(ny);
#pragma unroll
            for (int e = 0; e < 2; e++) {
                const float ma = rcp((c < 2 ? ny[2 * e] : nx[16 + 2 * e]) + 1e-6f);
                const float mb = rcp((c < 2 ? ny[2 * e + 1] : nx[17 + 2 * e]) + 1e-6f);
                const float ta = __shfl_xor_sync(0xffffffffu, ma, 2), tb = __shfl_xor_sync(0xffffffffu, mb, 2);
                const float r0 = c < 2 ? ta : ma, r1 = c < 2 ? tb : mb, r2 = c < 2 ? ma : ta, r3 = c < 2 ? mb : tb;
                const float r01 = c == 0 ? r0 : r1, r23 = c == 3 ? r3 : r2, r12 = c < 2 ? tb : ta;
                const int z = 2 * e;
                oa[0][0][0 + e] = pack(nx[z] * r0, nx[z + 1] * r0);
                oa[0][0][2 + e] = pack(nx[4 + z] * r0, nx[5 + z] * r0);
                oa[0][1][0 + e] = pack(nx[8 + z] * r01, nx[9 + z] * r01);
                oa[0][1][2 + e] = pack(nx[12 + z] * r1, nx[13 + z] * r1);
                oa[0][2][0 + e] = pack((c < 2 ? nx[16 + z] : ny[z]) * r12, (c < 2 ? nx[17 + z] : ny[z + 1]) * r12);
                oa[0][2][2 + e] = pack(ny[4 + z] * r2, ny[5 + z] * r2);
                oa[0][3][0 + e] = pack(ny[8 + z] * r23, ny[9 + z] * r23);
                oa[0][3][2 + e] = pack(ny[12 + z] * r3, ny[13 + z] * r3);
                oa[0][8][e] = pack(ny[16 + z] * r3, ny[17 + z] * r3);
            }
            if (w) bar_sync<1, 256>();
            SFOR(i, 0, 4) st128<i * 16384>((void*)p16, oa[0][i][0], oa[0][i][1], oa[0][i][2], oa[0][i][3]); SEND
            st64<0>((void*)p8, oa[0][8][0], oa[0][8][1]);
        }
        STAMPW(20 + w);
        if (w) {
            const unsigned c0 = clk();
            while (clk() - c0 < DELAY_LATE) {}
            bar_arrive<2, 256>();
        } else {
            bar_arrive<1, 256>();
            const unsigned c0 = clk();
            float ao[72];
            const uint64_t db = dz + desc(sb, 9216, 1024, 1), dp = dz + desc(sb, 9216, 27648, 1);
            auto o_step = [&](auto P, auto I) {
                constexpr int L = 1 - P.value, N = P.value ? 64 : 80;
                constexpr int B = I.value / 9, i = I.value % 9, O = (tile_o(2 * B + (i & 4) / 4) + L * 9216) / 16;
                if constexpr (i < 8) Mma<N>::template rs<(I.value > 0), O + (i & 3) * 128>(ao + 32 * L, oa[B][i], db);
                else Mma<N>::template rs<1, O + 512>(ao + 32 * L, oa[B][8], dp);
            };
            mbar_wait(bars + 8 * (B_FULL + 15));
            const uint64_t q16[3] = {p16 ^ 2048, (p16 ^ 4096) & ~2048ull, (p16 ^ 8192) & ~6144ull};
            const uint64_t q8[3] = {p8 ^ 1024, (p8 ^ 2048) & ~1024ull, (p8 ^ 4096) & ~3072ull};
            while (clk() - c0 < DELAY_EARLY) {}
            STAMPW(34);
            load_o<0>(oa[0], q16[0], q8[0]); load_o<1>(oa[1], q16[1], q8[1]);
            wg_fence();
            SFOR(i, 0, 4) o_step(IC<0>, IC<i>); o_step(IC<1>, IC<i>); SEND
            wg_commit();
            wg_wait<0>();
            SFOR(H, 0, 2)
                mbar_wait(bars + 8 * (B_FULL + 16 + H));
                int n = 0;
#pragma unroll 1
                for (; n < SPIN_LIMIT; n++) {
                    if (n > 0) { load_o<2 * H>(oa[2 * H], q16[2 * H], q8[2 * H]); load_o<2 * H + 1>(oa[2 * H + 1], q16[H + 1], q8[H + 1]); }
                    if (__all_sync(0xffffffffu, max(max_o<2 * H>(oa[2 * H]), max_o<1>(oa[2 * H + 1])) != SENT)) break;
                }
                STAMPW(22 + 2 * H);
                if constexpr (H == 0) {
                    bar_sync<2, 256>();
                    load_o<2>(oa[2], q16[2], q8[2]); load_o<3>(oa[3], q16[2], q8[2]);
                    wg_fence();
                    SFOR(i, 4, 18) o_step(IC<0>, IC<i>); o_step(IC<1>, IC<i>); SEND
                    wg_commit();
                }
            SEND
            const int l2 = t2 & 31;
            const uint32_t mb = sb + q * 4096, tb = sb + 16384 + q * 512;
            const uint32_t ro = mb + (l2 & 15) * 128, sw = ((l2 >> 4) ^ (l2 & 7)) << 4;
            int row0 = r * 128 + hh * 64 + q * 16, cl = cb * 128, ct = 512 + cb * 16;
            asm volatile("" : "+r"(row0), "+r"(cl), "+r"(ct));
            auto stage = [&](auto LO, auto HI) {
#pragma unroll
                for (int j = 8 * LO.value; j < 8 * HI.value; j++) asm volatile("" : "+f"(ao[j]) :: "memory");
#pragma unroll
                for (int i = LO.value; i < HI.value; i++) {
                    const float* a = ao + 8 * i;
                    stsm4(i < 8 ? ro + (i >> 2) * 2048 + (sw ^ (32 * (i & 3))) : tb + (l2 & 15) * 32 + (l2 >> 4) * 16,
                          pack(a[0], a[1]), pack(a[2], a[3]), pack(a[4], a[5]), pack(a[6], a[7]));
                }
            };
            auto o_steps = [&](auto P, auto LO, auto HI) { wg_fence(); SFOR(i, LO.value, HI.value) o_step(P, IC<i>); SEND wg_commit(); };
            o_steps(IC<0>, IC<18>, IC<36>);
            o_steps(IC<1>, IC<18>, IC<18 + O_K>);
            wg_wait<1>();
            bar_sync<3, 128>();
            STAMPW(28);
            stage(IC<4>, IC<9>);
            o_steps(IC<1>, IC<18 + O_K>, IC<18 + O_K2>);
            fence_async();
            __syncwarp();
            if (lead) { tma_st2(&mp.out, mb + 2048, cl + 64, row0); tma_st2(&mp.outt, tb, ct, row0); }
            if constexpr (O_K2 < 18) o_steps(IC<1>, IC<18 + O_K2>, IC<36>);
            wg_wait<0>();
            STAMPW(30);
            stage(IC<0>, IC<4>);
            fence_async();
            __syncwarp();
            if (lead) {
                tma_st2(&mp.out, mb, cl, row0);
                asm volatile("cp.async.bulk.commit_group;" ::: "memory");
                asm volatile("cp.async.bulk.wait_group.read 0;" ::: "memory");
            }
            STAMPW(32);
        }
        if (t == 0) { DUMP(w, 40, 2); }
    }
}

typedef CUresult (*EncodeFn)(CUtensorMap*, CUtensorMapDataType, cuuint32_t, void*, const cuuint64_t*, const cuuint64_t*,
                             const cuuint32_t*, const cuuint32_t*, CUtensorMapInterleave, CUtensorMapSwizzle,
                             CUtensorMapL2promotion, CUtensorMapFloatOOBfill);

void encode(EncodeFn fn, CUtensorMap* m, const void* base, int rank, const cuuint64_t* dims, const cuuint64_t* strides,
            const cuuint32_t* box, CUtensorMapSwizzle sw) {
    const cuuint32_t es[4] = {1, 1, 1, 1};
    fn(m, CU_TENSOR_MAP_DATA_TYPE_BFLOAT16, rank, const_cast<void*>(base), dims, strides, box, es, CU_TENSOR_MAP_INTERLEAVE_NONE, sw,
       CU_TENSOR_MAP_L2_PROMOTION_L2_128B, CU_TENSOR_MAP_FLOAT_OOB_FILL_NONE);
}

}

extern "C" void kernel_launch(void* const* d_in, const int* in_sizes, int n_in, void* d_out, int out_size) {
    (void)in_sizes; (void)n_in; (void)out_size;
    static EncodeFn fn = nullptr;
    static Scratch* sc = nullptr;
    if (!fn) {
        void* p = nullptr;
        cudaDriverEntryPointQueryResult qr;
        cudaGetDriverEntryPoint("cuTensorMapEncodeTiled", &p, cudaEnableDefault, &qr);
        fn = (EncodeFn)p;
        cudaGetSymbolAddress(&p, g_scratch);
        sc = (Scratch*)(((uintptr_t)p + 16383) & ~(uintptr_t)16383);
        cudaFuncSetAttribute(lab_kernel, cudaFuncAttributeMaxDynamicSharedMemorySize, SMEM_BYTES);
        cudaFuncAttributes fa; int dev = 0, res = 0;
        cudaFuncGetAttributes(&fa, lab_kernel);
        cudaGetDevice(&dev);
        cudaDeviceGetAttribute(&res, cudaDevAttrReservedSharedMemoryPerBlock, dev);
        if (fa.sharedSizeBytes != 0 || res != 1024) sc = nullptr;
    }
    if (!sc) return;
    const void *x = d_in[0], *wqkv = d_in[1], *wo = d_in[2];
    constexpr Tabs zs = make_tabs();
    Maps mp;
    const auto SW = CU_TENSOR_MAP_SWIZZLE_128B;
    { cuuint64_t d[4] = {64, 2048, 1, 9}, s[3] = {1152, 128, 128}; cuuint32_t b[4] = {64, 128, 1, 1}; encode(fn, &mp.x, x, 4, d, s, b, SW); }
    { cuuint64_t d[4] = {1728, 64, 1, 9}, s[3] = {3456, 3456, 64 * 3456}; cuuint32_t b[4] = {64, 64, 1, 1}; encode(fn, &mp.w, wqkv, 4, d, s, b, SW); }
    { cuuint64_t d[4] = {576, 64, 3, 9}, s[3] = {3456, 1152, 64 * 3456}; cuuint32_t b[4] = {16, 64, 2, 1}; encode(fn, &mp.w16, wqkv, 4, d, s, b, CU_TENSOR_MAP_SWIZZLE_32B); }
    { cuuint64_t d[4] = {64, 72, 9, 8}, s[3] = {1152, 128, 72 * 1152}; cuuint32_t b[4] = {64, 72, 2, 1}; encode(fn, &mp.wo, wo, 4, d, s, b, SW); }
    { cuuint64_t d[4] = {576, 72, 1, 8}, s[3] = {1152, 1152, 72 * 1152}; cuuint32_t b[4] = {16, 72, 1, 1}; encode(fn, &mp.wot, wo, 4, d, s, b, SW); }
    { cuuint64_t d[2] = {576, 2048}, s[1] = {1152}; cuuint32_t b[2] = {64, 16}; encode(fn, &mp.out, d_out, 2, d, s, b, SW); }
    { cuuint64_t d[2] = {576, 2048}, s[1] = {1152}; cuuint32_t b[2] = {16, 16}; encode(fn, &mp.outt, d_out, 2, d, s, b, CU_TENSOR_MAP_SWIZZLE_NONE); }
    lab_kernel<<<dim3(2, 4, 16), 384, SMEM_BYTES, cudaStreamPerThread>>>(sc, zs, mp);
}
```
